```python
import torch

def _softmax(x, axis=-1):
    return torch.softmax(x, dim=axis)

def _gelu(x):
    return torch.nn.functional.gelu(x, approximate='tanh')

def _silu(x):
    return torch.nn.functional.silu(x)

def _sigmoid(x):
    return torch.sigmoid(x)

def _layernorm(x, axis=-1, eps=1e-05):
    m = x.mean(dim=axis, keepdim=True)
    v = x.var(dim=axis, keepdim=True, unbiased=False)
    return (x - m) / torch.sqrt(v + eps)

def _scatter_add(tgt, idx, src, axis=0):
    return tgt.clone().index_add_(axis, idx, src)

def _segment_sum(src, seg, n):
    out = torch.zeros((n,) + src.shape[1:], dtype=src.dtype)
    return out.index_add_(0, seg, src)

def _pad(x, pw):
    flat = tuple((v for pair in reversed(pw) for v in pair))
    return torch.nn.functional.pad(x, flat)
kernel_name = 'adaLN_cond__gqa_block_cached__geglu_ffn__decode'

def setup_inputs():

    _w = lambda a: (lambda t: t.to(torch.bfloat16) if t.is_floating_point() else t)(torch.as_tensor(a))

    def _A_setup():
        B, Sq, D = (4, 1, 576)
        Hq, Hkv, Sk, Dh = (32, 16, 4096, 128)
        assert Hq % Hkv == 0, (Hq, Hkv)
        return {'x': _w((lambda *s: torch.randn(*s, dtype=torch.bfloat16) * 0.1)(B, Sq, D)), 'k_cache': _w((lambda *s: torch.randn(*s, dtype=torch.bfloat16) * 0.8)(B, Hkv, Sk, Dh)), 'v_cache': _w((lambda *s: torch.randn(*s, dtype=torch.bfloat16) * 1.6)(B, Hkv, Sk, Dh)), 'wq': _w((lambda *s: torch.randn(*s, dtype=torch.bfloat16) * 0.8)(D, Hq * Dh) * D ** (-0.5)), 'wo': _w((lambda *s: torch.randn(*s, dtype=torch.bfloat16) * 1.6)(Hq * Dh, D) * (Hq * Dh) ** (-0.5))}
    _A_in = _A_setup()

    def _B_setup():
        B, S, D, F = (4, 1, 576, 4608)
        return {'x': _w((lambda *s: torch.randn(*s, dtype=torch.bfloat16) * 0.1)(B, S, D)), 'w_gate': _w((lambda *s: torch.randn(*s, dtype=torch.bfloat16) * 0.1)(D, F)), 'w_up': _w((lambda *s: torch.randn(*s, dtype=torch.bfloat16) * 0.1)(D, F)), 'w_down': _w((lambda *s: torch.randn(*s, dtype=torch.bfloat16) * 0.1)(F, D))}
    _B_in = _B_setup()
    return {'A_x': _A_in['x'], 'A_k_cache': _A_in['k_cache'], 'A_v_cache': _A_in['v_cache'], 'A_wq': _A_in['wq'], 'A_wo': _A_in['wo'], 'B_x': _B_in['x'], 'B_w_gate': _B_in['w_gate'], 'B_w_up': _B_in['w_up'], 'B_w_down': _B_in['w_down'], 'c': _w((lambda *s: torch.randn(*s, dtype=torch.bfloat16) * 0.8)(4, 576) * 8.0), 'w_mod': _w((lambda *s: torch.randn(*s, dtype=torch.bfloat16) * 0.8)(576, 6 * 576) * 576 ** (-0.5) * 8.0)}

def reference(A_x, A_k_cache, A_v_cache, A_wq, A_wo, B_x, B_w_gate, B_w_up, B_w_down, c, w_mod):

    def _A_ref(x, k_cache, v_cache, wq, wo):
        B, Sq, D = x.shape
        Hq, Dh = (32, 128)
        Hkv = k_cache.shape[1]
        rep = Hq // Hkv
        q = (lambda x, *d: x.permute(*d))((x @ wq).reshape(B, Sq, Hq, Dh), 0, 2, 1, 3)
        k = (lambda x, n, axis: torch.repeat_interleave(x, n, dim=axis))(k_cache, rep, axis=1)
        v = (lambda x, n, axis: torch.repeat_interleave(x, n, dim=axis))(v_cache, rep, axis=1)
        scores = torch.einsum('bhqd,bhkd->bhqk', q, k) * Dh ** (-0.5)
        p = _softmax(scores, axis=-1)
        o = torch.einsum('bhqk,bhkd->bhqd', p, v)
        return (lambda x, *d: x.permute(*d))(o, 0, 2, 1, 3).reshape(B, Sq, Hq * Dh) @ wo

    def _B_ref(x, w_gate, w_up, w_down):
        return _gelu(x @ w_gate) * (x @ w_up) @ w_down
    x = A_x
    mod = (_silu(c) @ w_mod).reshape(c.shape[0], 6, 1, -1)
    sa, ca, ga, sb, cb, gb = (mod[:, 0].clone(), mod[:, 1].clone(), mod[:, 2].clone(), mod[:, 3].clone(), mod[:, 4].clone(), mod[:, 5].clone())
    h = _layernorm(x, axis=-1) * (1 + ca) + sa
    x = x + ga * _A_ref(h, A_k_cache, A_v_cache, A_wq, A_wo)
    h = _layernorm(x, axis=-1) * (1 + cb) + sb
    x = x + gb * _B_ref(h, B_w_gate, B_w_up, B_w_down)
    return x
```

```cpp
#include <cuda_runtime.h>
#include <cuda_bf16.h>
#include <cuda.h>
#include <stdint.h>

namespace {

constexpr int D_MODEL = 576;
constexpr int N_MOD = 6 * D_MODEL;
constexpr int HQD = 4096;
constexpr int FF = 4608;
constexpr int NCTA = 128;
constexpr int NTHREADS = 512;
constexpr int NSLOT = 13;
constexpr int SLOT = 16384;
constexpr int RING = NSLOT * SLOT;
constexpr int NKV = 64;
constexpr int APITCH = 584;
constexpr int PRO_OFF = 8 * SLOT;

constexpr int OFF_BAR = 0;
constexpr int OFF_ACT = 512;
constexpr int OFF_RED = OFF_ACT + 4672;
constexpr int OFF_Q = OFF_RED + 10496;
constexpr int OFF_A2 = OFF_Q + 576;
constexpr int OFF_X1 = OFF_A2 + 384;
constexpr int MISC = OFF_X1 + 128;
constexpr int SMEM_BYTES = RING + MISC + 1024;

constexpr int B_FULL = 0, B_EMPTY = 13, B_MOD = 26, B_WQ = 27, B_PROFREE = 28, B_WO = 29  , B_GU = 33  , B_DN = 39  , B_COUNT = 42;

struct Maps {
    CUtensorMap k, v, wmod, wq, wo, g32, u32, g40, u40, wd;
};
constexpr int MAXOPS = 80;
struct Sched {
    uint2 ops[3][MAXOPS];
    int nops[3];
    int prewrite;
    int prewrite0, prewrite2;
    unsigned char slot[NKV];
};

__device__ unsigned g_epoch;
__device__ __align__(128) unsigned g_mod[4 * N_MOD];
__device__ __align__(128) unsigned g_q[4 * HQD];
__device__ __align__(128) unsigned long long g_o[NCTA * 72];
__device__ __align__(128) unsigned g_y[2 * 4 * D_MODEL];
__device__ __align__(128) unsigned g_d[72 * NCTA * 32];
#define TRACE(i) do {} while (0)
#define OPTRACE(n, k) do {} while (0)

constexpr int SPIN_LIMIT = 1 << 22;

__device__ __forceinline__ uint64_t gtime() { uint64_t t; asm volatile("mov.u64 %0, %%globaltimer;" : "=l"(t)); return t; }
__device__ __forceinline__ uint32_t gtime32() { uint32_t t; asm volatile("mov.u32 %0, %%globaltimer_lo;" : "=r"(t)); return t; }
__device__ __forceinline__ uint32_t smem_u32(const void* p) { return (uint32_t)__cvta_generic_to_shared(p); }
__device__ __forceinline__ void mbar_init(uint32_t bar, uint32_t cnt) { asm volatile("mbarrier.init.shared::cta.b64 [%0], %1;" :: "r"(bar), "r"(cnt) : "memory"); }
__device__ __forceinline__ void mbar_expect_tx(uint32_t bar, uint32_t bytes) { asm volatile("mbarrier.arrive.expect_tx.shared::cta.b64 _, [%0], %1;" :: "r"(bar), "r"(bytes) : "memory"); }
__device__ __forceinline__ void mbar_arrive(uint32_t bar) { asm volatile("mbarrier.arrive.shared::cta.b64 _, [%0];" :: "r"(bar) : "memory"); }
__device__ __forceinline__ bool mbar_try_wait(uint32_t bar, uint32_t parity) {
    uint32_t ok;
    asm volatile("{\n.reg .pred p;\nmbarrier.try_wait.parity.shared::cta.b64 p, [%1], %2;\nselp.u32 %0, 1, 0, p;\n}" : "=r"(ok) : "r"(bar), "r"(parity) : "memory");
    return ok;
}
__device__ __forceinline__ void mbar_wait(uint32_t bar, uint32_t parity) {
    int it = 0;
#pragma unroll 1
    while (!mbar_try_wait(bar, parity)) { if (++it > SPIN_LIMIT) __trap(); }
}
__device__ __forceinline__ void tma2d(uint32_t dst, const CUtensorMap* m, int c0, int c1, uint32_t bar) {
    asm volatile("cp.async.bulk.tensor.2d.shared::cluster.global.mbarrier::complete_tx::bytes [%0], [%1, {%3, %4}], [%2];" :: "r"(dst), "l"(m), "r"(bar), "r"(c0), "r"(c1) : "memory");
}
__device__ __forceinline__ void tma3d(uint32_t dst, const CUtensorMap* m, int c0, int c1, int c2, uint32_t bar) {
    asm volatile("cp.async.bulk.tensor.3d.shared::cluster.global.mbarrier::complete_tx::bytes [%0], [%1, {%3, %4, %5}], [%2];" :: "r"(dst), "l"(m), "r"(bar), "r"(c0), "r"(c1), "r"(c2) : "memory");
}
__device__ __forceinline__ void ldsm4(uint32_t (&r)[4], uint32_t addr) {
    asm volatile("ldmatrix.sync.aligned.m8n8.x4.shared.b16 {%0,%1,%2,%3}, [%4];" : "=r"(r[0]), "=r"(r[1]), "=r"(r[2]), "=r"(r[3]) : "r"(addr) : "memory");
}
__device__ __forceinline__ void ldsm4t(uint32_t (&r)[4], uint32_t addr) {
    asm volatile("ldmatrix.sync.aligned.m8n8.x4.trans.shared.b16 {%0,%1,%2,%3}, [%4];" : "=r"(r[0]), "=r"(r[1]), "=r"(r[2]), "=r"(r[3]) : "r"(addr) : "memory");
}
__device__ __forceinline__ void ldsm2t(uint32_t (&r)[2], uint32_t addr) {
    asm volatile("ldmatrix.sync.aligned.m8n8.x2.trans.shared.b16 {%0,%1}, [%2];" : "=r"(r[0]), "=r"(r[1]) : "r"(addr) : "memory");
}
__device__ __forceinline__ void mma16816(float (&c)[4], const uint32_t (&a)[4], uint32_t b0, uint32_t b1) {
    asm volatile("mma.sync.aligned.m16n8k16.row.col.f32.bf16.bf16.f32 {%0,%1,%2,%3}, {%4,%5,%6,%7}, {%8,%9}, {%0,%1,%2,%3};"
                 : "+f"(c[0]), "+f"(c[1]), "+f"(c[2]), "+f"(c[3]) : "r"(a[0]), "r"(a[1]), "r"(a[2]), "r"(a[3]), "r"(b0), "r"(b1));
}
__device__ __forceinline__ void mma1688(float (&c)[4], const uint32_t (&a)[2], uint32_t b0) {
    asm volatile("mma.sync.aligned.m16n8k8.row.col.f32.bf16.bf16.f32 {%0,%1,%2,%3}, {%4,%5}, {%6}, {%0,%1,%2,%3};"
                 : "+f"(c[0]), "+f"(c[1]), "+f"(c[2]), "+f"(c[3]) : "r"(a[0]), "r"(a[1]), "r"(b0));
}
__device__ __forceinline__ uint32_t movtrans(uint32_t a) {
    uint32_t d; asm volatile("movmatrix.sync.aligned.m8n8.trans.b16 %0, %1;" : "=r"(d) : "r"(a)); return d;
}
__device__ __forceinline__ uint32_t lds32(uint32_t addr) { uint32_t v; asm volatile("ld.shared.b32 %0, [%1];" : "=r"(v) : "r"(addr) : "memory"); return v; }
__device__ __forceinline__ void cbar() { asm volatile("bar.sync 1, 256;" ::: "memory"); }

__device__ __forceinline__ uint32_t pack_bf2(float lo, float hi) {
    uint32_t r; asm("cvt.rn.bf16x2.f32 %0, %1, %2;" : "=r"(r) : "f"(hi), "f"(lo)); return r;
}
__device__ __forceinline__ uint32_t bmul2(uint32_t a, uint32_t b) { uint32_t r; asm("mul.rn.bf16x2 %0, %1, %2;" : "=r"(r) : "r"(a), "r"(b)); return r; }
__device__ __forceinline__ uint32_t badd2(uint32_t a, uint32_t b) { uint32_t r; asm("add.rn.bf16x2 %0, %1, %2;" : "=r"(r) : "r"(a), "r"(b)); return r; }
__device__ __forceinline__ uint32_t bsub2(uint32_t a, uint32_t b) { uint32_t r; asm("sub.rn.bf16x2 %0, %1, %2;" : "=r"(r) : "r"(a), "r"(b)); return r; }
__device__ __forceinline__ float bf_lo(uint32_t w) { return __uint_as_float(w << 16); }
__device__ __forceinline__ float bf_hi(uint32_t w) { return __uint_as_float(w & 0xffff0000u); }

__device__ __forceinline__ float bfr(float x) { return __uint_as_float(pack_bf2(0.f, x)); }
__device__ __forceinline__ uint32_t ld_rlx32(const void* p) { uint32_t v; asm volatile("ld.relaxed.gpu.global.b32 %0, [%1];" : "=r"(v) : "l"(p) : "memory"); return v; }
__device__ __forceinline__ uint4 ld_rlx128(const void* p) {
    uint4 v; asm volatile("ld.relaxed.gpu.global.v4.b32 {%0,%1,%2,%3}, [%4];" : "=r"(v.x), "=r"(v.y), "=r"(v.z), "=r"(v.w) : "l"(p) : "memory"); return v;
}
__device__ __forceinline__ ulonglong2 ld_rlx2x64(const void* p) {
    ulonglong2 v; asm volatile("ld.relaxed.gpu.global.v2.b64 {%0,%1}, [%2];" : "=l"(v.x), "=l"(v.y) : "l"(p) : "memory"); return v;
}
__device__ __forceinline__ unsigned long long ld_rlx64(const void* p) {
    unsigned long long v; asm volatile("ld.relaxed.gpu.global.b64 %0, [%1];" : "=l"(v) : "l"(p) : "memory"); return v;
}
__device__ __forceinline__ float ex2(float x) { float r; asm("ex2.approx.ftz.f32 %0, %1;" : "=f"(r) : "f"(x)); return r; }
__device__ __forceinline__ void st_rlx32(void* p, uint32_t v) { asm volatile("st.relaxed.gpu.global.b32 [%0], %1;" :: "l"(p), "r"(v) : "memory"); }
__device__ __forceinline__ void st_rlx2x32(void* p, uint32_t a, uint32_t b) { asm volatile("st.relaxed.gpu.global.v2.b32 [%0], {%1,%2};" :: "l"(p), "r"(a), "r"(b) : "memory"); }
__device__ __forceinline__ void st_rlx4x32(void* p, uint32_t a) { asm volatile("st.relaxed.gpu.global.v4.b32 [%0], {%1,%1,%1,%1};" :: "l"(p), "r"(a) : "memory"); }
__device__ __forceinline__ void st_rlx64(void* p, unsigned long long v) { asm volatile("st.relaxed.gpu.global.b64 [%0], %1;" :: "l"(p), "l"(v) : "memory"); }
__device__ __forceinline__ uint32_t tagf(float x, uint32_t tag) { return (__float_as_uint(x) & ~1u) | tag; }

__device__ __forceinline__ uint32_t xor_or(uint32_t a, uint32_t b, uint32_t t) {
    uint32_t r; asm("lop3.b32 %0, %1, %2, %3, 0x7E;" : "=r"(r) : "r"(a), "r"(b), "r"(t)); return r;
}
__device__ __forceinline__ uint32_t or_and1(uint32_t a, uint32_t b) {
    uint32_t r; asm("lop3.b32 %0, %1, %2, 1, 0xA8;" : "=r"(r) : "r"(a), "r"(b)); return r;
}
__device__ __forceinline__ void ld_rlx128_if(uint4& v, const void* p, uint32_t cond) {
    asm volatile("{\n.reg .pred p;\nsetp.ne.u32 p, %5, 0;\n@p ld.relaxed.gpu.global.v4.b32 {%0,%1,%2,%3}, [%4];\n}"
                 : "+r"(v.x), "+r"(v.y), "+r"(v.z), "+r"(v.w) : "l"(p), "r"(cond) : "memory");
}
__device__ __forceinline__ void ld_rlx2x64_if(uint4& v, const void* p, uint32_t cond) {
    asm volatile("{\n.reg .pred p;\n.reg .b64 a, b;\nsetp.ne.u32 p, %5, 0;\nmov.b64 a, {%0,%1};\nmov.b64 b, {%2,%3};\n"
                 "@p ld.relaxed.gpu.global.v2.b64 {a, b}, [%4];\nmov.b64 {%0,%1}, a;\nmov.b64 {%2,%3}, b;\n}"
                 : "+r"(v.x), "+r"(v.y), "+r"(v.z), "+r"(v.w) : "l"(p), "r"(cond) : "memory");
}
template <int N, bool W64, typename F>
__device__ __forceinline__ void gather128(uint4 (&v)[N], F addr, uint32_t tag) {
    uint32_t bad[N];
#pragma unroll
    for (int i = 0; i < N; i++) { bad[i] = 1u; v[i] = make_uint4(0u, 0u, 0u, 0u); }
    int it = 0;
#pragma unroll 1
    while (true) {
#pragma unroll
        for (int i = 0; i < N; i++) { if (W64) ld_rlx2x64_if(v[i], addr(i), bad[i]); else ld_rlx128_if(v[i], addr(i), bad[i]); }
        uint32_t any = 0u;
#pragma unroll
        for (int i = 0; i < N; i++) {
            bad[i] = W64 ? (xor_or(v[i].x, v[i].z, tag) & 1u) : or_and1(xor_or(v[i].x, v[i].y, tag), xor_or(v[i].z, v[i].w, tag));
            any |= bad[i];
        }
        if (any == 0u) break;
        if (++it > SPIN_LIMIT) __trap();
    }
}
__device__ __forceinline__ void wait_any(const unsigned* p, uint32_t ntag) {
    int it = 0;
#pragma unroll 1
    while (true) {
        const uint32_t v = ld_rlx32(p);
        if ((v ^ ntag) & 1u) break;
        if (++it > SPIN_LIMIT) __trap();
    }
}
__global__ void __launch_bounds__(NTHREADS, 1)
fused_decode_kernel(const __grid_constant__ Maps maps, const __grid_constant__ Sched tune,
                    const __nv_bfloat16* __restrict__ gx, const __nv_bfloat16* __restrict__ gc,
                    __nv_bfloat16* __restrict__ gout) {
    extern __shared__ unsigned char smem_raw[];
    const uint32_t sbase = (smem_u32(smem_raw) + 1023u) & ~1023u;
    unsigned char* sgen = smem_raw + (sbase - smem_u32(smem_raw));
    const uint32_t misc = sbase + RING;
    auto bar = [&](int i) -> uint32_t { return misc + OFF_BAR + 8 * i; };

    const int tid = threadIdx.x, warp = tid >> 5, lane = tid & 31;
    const int cta = blockIdx.x;
    const bool wide = cta & 1;
    const int fw = wide ? 40 : 32;
    const bool is_wo = !wide || cta < 16;
    const int wou = wide ? 64 + (cta >> 1) : (cta >> 1);
    const int modb = wide ? (cta >> 1) - 8 : 44 + (cta >> 1);
    const bool has_mod = wide ? cta >= 16 : cta >= 24;
    const uint32_t gu_off = is_wo ? 65536u : 0u;
    const uint32_t boxb = 192u * fw * 2u;
    const uint32_t dn_off = gu_off + 6 * boxb;
    const int rid = cta - 56;
    const float LOG2E = 1.4426950408889634f;

    if (warp >= 12) {
        asm volatile("setmaxnreg.dec.sync.aligned.u32 40;");
        if (warp > 12) return;
        const int fcol0 = 72 * (cta >> 1) + (wide ? 32 : 0);
        const int cls = wide ? (is_wo ? 2 : 1) : 0;
        uint2 ent[3];
#pragma unroll
        for (int r = 0; r < 3; r++) {
            const int m = min(32 * r + lane, MAXOPS - 1);
            asm volatile("ld.v2.u32 {%0,%1}, [%2];" : "=r"(ent[r].x), "=r"(ent[r].y) : "l"(&tune.ops[cls][m]));
        }
        if (lane == 0) {
            for (int i = 0; i < B_COUNT; i++) mbar_init(bar(i), (i >= B_EMPTY && i < B_MOD) ? 4 : (i == B_PROFREE ? 8 : 1));
            asm volatile("fence.mbarrier_init.release.cluster;" ::: "memory");
            asm volatile("fence.proxy.async.shared::cta;" ::: "memory");
        } else if (lane < 11) {
            asm volatile("prefetch.tensormap [%0];" :: "l"(&maps.k + (lane - 1)) : "memory");
        }
        __syncwarp();
        const uint32_t t0 = gtime32();
        if (lane == 0) {
            TRACE(0);
            if (has_mod) {
                mbar_expect_tx(bar(B_MOD), 36864);
                for (int j = 0; j < 3; j++) tma2d(sbase + PRO_OFF + j * 12288, &maps.wmod, 32 * modb, 192 * j, bar(B_MOD));
            } else {
                mbar_arrive(bar(B_MOD));
            }
            mbar_expect_tx(bar(B_WQ), 36864);
            for (int j = 0; j < 3; j++) tma2d(sbase + PRO_OFF + 36864 + j * 12288, &maps.wq, 32 * cta, 192 * j, bar(B_WQ));
        }
        asm volatile("bar.arrive 2, 288;" ::: "memory");
        const int row0 = (((cta >> 1) & 3) * 16 + (cta >> 3)) * 4096 + (cta & 1) * 64;
        const int nops = tune.nops[cls];
#pragma unroll 1
        for (int r = 0; r < 3; r++) {
            const uint2 e = r == 0 ? ent[0] : (r == 1 ? ent[1] : ent[2]);
            const int op = (e.y >> 8) & 255, tj = op - 64;
            const uint32_t dst = sbase + (e.y & 255u) * 1024u;
            const uint32_t fb = bar((e.x >> 24) & 127u);
            const CUtensorMap* mp;
            int c0 = 0, c1, c1b = -1, dim3;
            uint32_t bytes, dstb = 0;
            if (op < 64) { mp = &maps.k + (op & 1); c1 = row0 + (op >> 1) * 128; bytes = SLOT; dim3 = 1; }
            else if (tj < 4) { mp = &maps.wo; c0 = 16 * (wou >> 1); c1 = 2048 * (wou & 1) + 512 * tj; c1b = c1 + 256; dstb = dst + 8192; bytes = 16384; dim3 = 0; }
            else if (tj < 10) { mp = &maps.g32 + (tj & 1) + (wide ? 2 : 0); c0 = fcol0; c1 = 192 * ((tj - 4) >> 1); bytes = boxb; dim3 = 0; }
            else { mp = &maps.wd; c1 = fcol0 + 16 * (tj - 10); bytes = 9216; dim3 = 1; if (tj < 12) { c1b = c1 + 8; dstb = dst + 9216; bytes = 18432; } }
            const uint32_t tmin = e.y >> 16;
            const int cnt = min(32, nops - 32 * r);
#pragma unroll 1
            for (int l = 0; l < cnt; l++) {
                if (lane == l) {
                    if ((e.x & 127u) != 127u) mbar_wait(bar(e.x & 127u), (e.x >> 7) & 1u);
                    if (((e.x >> 8) & 127u) != 127u) mbar_wait(bar((e.x >> 8) & 127u), (e.x >> 15) & 1u);
                    if (((e.x >> 16) & 127u) != 127u) mbar_wait(bar((e.x >> 16) & 127u), (e.x >> 23) & 1u);
                    if (tmin) while (gtime32() - t0 < tmin) {}
                    mbar_expect_tx(fb, bytes);
                    if (dim3) { tma3d(dst, mp, 0, c1, 0, fb); if (c1b >= 0) tma3d(dstb, mp, 0, c1b, 0, fb); }
                    else { tma2d(dst, mp, c0, c1, fb); if (c1b >= 0) tma2d(dstb, mp, c0, c1b, fb); }
                    OPTRACE(32 * r + l, 2);
                    if (op == 63) TRACE(1);
                }
                __syncwarp();
            }
        }
        if (lane == 0) TRACE(2);
        return;
    }

    const uint32_t epoch = ld_rlx32(&g_epoch);
    float* red = reinterpret_cast<float*>(sgen + RING + OFF_RED);

    if (warp >= 8) {
        asm volatile("setmaxnreg.dec.sync.aligned.u32 120;");
        const int b = warp - 8;
        const bool q4 = lane < 16;
        const int ql = 4 * lane, q4off = 512 + 4 * (lane & 15) - ql;
        auto qoff = [&](int i) -> int { return i < 4 ? 128 * i : q4off; };
        uint2 xw[5], cw[5];
#pragma unroll
        for (int i = 0; i < 5; i++) {
            xw[i] = *reinterpret_cast<const uint2*>(gx + b * D_MODEL + ql + qoff(i));
            cw[i] = *reinterpret_cast<const uint2*>(gc + b * D_MODEL + ql + qoff(i));
        }
        unsigned char* arow = sgen + RING + OFF_ACT + (b * APITCH + ql) * 2;
#pragma unroll
        for (int i = 0; i < 5; i++) {
            const float c0 = bf_lo(cw[i].x), c1 = bf_hi(cw[i].x), c2 = bf_lo(cw[i].y), c3 = bf_hi(cw[i].y);
            *reinterpret_cast<uint2*>(arow + qoff(i) * 2) =
                make_uint2(pack_bf2(__fdividef(c0, 1.0f + ex2(-LOG2E * c0)), __fdividef(c1, 1.0f + ex2(-LOG2E * c1))),
                           pack_bf2(__fdividef(c2, 1.0f + ex2(-LOG2E * c2)), __fdividef(c3, 1.0f + ex2(-LOG2E * c3))));
        }
        asm volatile("bar.arrive 3, 384;" ::: "memory");
        const uint32_t ntag = epoch & 1u;
        uint32_t gbw = 0;
#pragma unroll 1
        for (int ph = 0; ph < 2; ph++) {
            const unsigned* pm = &g_mod[b * N_MOD + ph * 3 * D_MODEL + ql];
            uint2 shp[5], scp[5];
            {
                wait_any(&g_mod[b * N_MOD + ph * 3 * D_MODEL + 8 * cta], ntag);
                uint4 mv[10];
                gather128<10, false>(mv, [&](int i) { return pm + qoff(i % 5) + (i / 5) * D_MODEL; }, ntag ^ 1u);
#pragma unroll
                for (int i = 0; i < 5; i++) {
                    shp[i] = make_uint2(__byte_perm(mv[i].x, mv[i].y, 0x7632), __byte_perm(mv[i].z, mv[i].w, 0x7632));
                    scp[i] = make_uint2(badd2(0x3f803f80u, __byte_perm(mv[i + 5].x, mv[i + 5].y, 0x7632)), badd2(0x3f803f80u, __byte_perm(mv[i + 5].z, mv[i + 5].w, 0x7632)));
                }
            }
            if (ph == 1) {
                uint2 gap[5];
                {
                    uint4 mv[5];
                    gather128<5, false>(mv, [&](int i) { return pm + qoff(i) - D_MODEL; }, ntag ^ 1u);
#pragma unroll
                    for (int i = 0; i < 5; i++) gap[i] = make_uint2(__byte_perm(mv[i].x, mv[i].y, 0x7632), __byte_perm(mv[i].z, mv[i].w, 0x7632));
                }
                if (rid >= 0) {
                    const unsigned* pg = &g_mod[(lane & 3) * N_MOD + 5 * D_MODEL + 8 * rid + (lane >> 2)];
                    int it = 0;
#pragma unroll 1
                    do { gbw = ld_rlx32(pg); if (++it > SPIN_LIMIT) __trap(); } while ((gbw & 1u) == ntag);
                }
                asm volatile("bar.sync 7, 384;" ::: "memory");
                if (tune.prewrite2) {
#pragma unroll
                    for (int i = 0; i < 5; i++) {
                        const int e = tid - 256 + 128 * i;
                        if (e < 576) st_rlx4x32(&g_d[((e >> 3) * NCTA + cta) * 32 + (e & 7) * 4], ntag);
                    }
                }
                const unsigned* py = &g_y[b * D_MODEL + ql];
                wait_any(&g_y[(((cta >> 1) & 1) * 4 + b) * D_MODEL + 16 * (cta >> 2)], ntag);
                uint4 yv[10];
                gather128<10, false>(yv, [&](int i) { return py + qoff(i % 5) + (i / 5) * 4 * D_MODEL; }, ntag ^ 1u);
                __syncwarp();
                if (lane == 0 && b == 0) TRACE(22);
#pragma unroll
                for (int i = 0; i < 5; i++) {
                    const uint32_t y01 = pack_bf2(__uint_as_float(yv[i].x) + __uint_as_float(yv[i + 5].x), __uint_as_float(yv[i].y) + __uint_as_float(yv[i + 5].y));
                    const uint32_t y23 = pack_bf2(__uint_as_float(yv[i].z) + __uint_as_float(yv[i + 5].z), __uint_as_float(yv[i].w) + __uint_as_float(yv[i + 5].w));
                    xw[i] = make_uint2(badd2(xw[i].x, bmul2(gap[i].x, y01)), badd2(xw[i].y, bmul2(gap[i].y, y23)));
                }
            } else {
                asm volatile("bar.sync 6, 384;" ::: "memory");
            }
            const float x0 = bf_lo(__shfl_sync(0xffffffffu, xw[0].x, 0));
            float s1[5], s2[5];
#pragma unroll
            for (int i = 0; i < 5; i++) {
                const float d0 = bf_lo(xw[i].x) - x0, d1 = bf_hi(xw[i].x) - x0, d2 = bf_lo(xw[i].y) - x0, d3 = bf_hi(xw[i].y) - x0;
                s1[i] = (d0 + d1) + (d2 + d3);
                s2[i] = fmaf(d0, d0, d1 * d1) + fmaf(d2, d2, d3 * d3);
            }
            float sa = ((s1[0] + s1[1]) + (s1[2] + s1[3])) + (q4 ? s1[4] : 0.f);
            float sb = ((s2[0] + s2[1]) + (s2[2] + s2[3])) + (q4 ? s2[4] : 0.f);
#pragma unroll
            for (int o = 16; o > 0; o >>= 1) { sa += __shfl_xor_sync(0xffffffffu, sa, o); sb += __shfl_xor_sync(0xffffffffu, sb, o); }
            sa *= (1.0f / 576.0f);
            const float mean = x0 + sa;
            const float var = bfr(fmaxf(fmaf(-sa, sa, sb * (1.0f / 576.0f)), 0.f));
            const uint32_t mb2 = pack_bf2(mean, mean);
            float sq; asm("sqrt.approx.f32 %0, %1;" : "=f"(sq) : "f"(bfr(var + 1e-5f)));
            const float rden = __fdividef(1.0f, bfr(sq));
#pragma unroll
            for (int i = 0; i < 5; i++) {
                const uint32_t d01 = bsub2(xw[i].x, mb2), d23 = bsub2(xw[i].y, mb2);
                const uint32_t n01 = pack_bf2(bf_lo(d01) * rden, bf_hi(d01) * rden), n23 = pack_bf2(bf_lo(d23) * rden, bf_hi(d23) * rden);
                *reinterpret_cast<uint2*>(arow + qoff(i) * 2) = make_uint2(badd2(bmul2(n01, scp[i].x), shp[i].x), badd2(bmul2(n23, scp[i].y), shp[i].y));
            }
            asm volatile("bar.arrive %0, 384;" :: "r"(4 + ph) : "memory");
        }
        if (lane == 0 && b == 0) TRACE(10);
        if (rid >= 0) {
            uint2* x1s = reinterpret_cast<uint2*>(sgen + RING + OFF_X1);
#pragma unroll
            for (int i = 0; i < 5; i++) {
                const int q = (ql + qoff(i)) >> 2;
                if ((q >> 1) == rid) x1s[b * 2 + (q & 1)] = xw[i];
            }
            asm volatile("bar.sync 8, 384;" ::: "memory");
            const unsigned* pd = &g_d[rid * NCTA * 32 + (tid - 256) * 4];
            uint4 v[8];
            gather128<8, false>(v, [&](int i) { return pd + i * 512; }, ntag ^ 1u);
            __syncwarp();
            float s0 = 0.f, s1 = 0.f, s2 = 0.f, s3 = 0.f;
#pragma unroll
            for (int i = 0; i < 8; i++) {
                s0 += __uint_as_float(v[i].x); s1 += __uint_as_float(v[i].y); s2 += __uint_as_float(v[i].z); s3 += __uint_as_float(v[i].w);
            }
#pragma unroll
            for (int of = 8; of < 32; of <<= 1) {
                s0 += __shfl_xor_sync(0xffffffffu, s0, of); s1 += __shfl_xor_sync(0xffffffffu, s1, of);
                s2 += __shfl_xor_sync(0xffffffffu, s2, of); s3 += __shfl_xor_sync(0xffffffffu, s3, of);
            }
            if (lane < 8) *reinterpret_cast<float4*>(red + b * 32 + lane * 4) = make_float4(s0, s1, s2, s3);
            asm volatile("bar.sync 9, 128;" ::: "memory");
            if (b == 0) {
                const float s = (red[lane] + red[32 + lane]) + (red[64 + lane] + red[96 + lane]);
                const float x1 = __bfloat162float(reinterpret_cast<const __nv_bfloat16*>(x1s)[(lane & 3) * 8 + (lane >> 2)]);
                gout[(lane & 3) * D_MODEL + 8 * rid + (lane >> 2)] = __float2bfloat16_rn(x1 + bfr(bf_hi(gbw) * bfr(s)));
                if (rid == 0 && lane == 0) g_epoch = epoch + 1u;
                if (lane == 0) TRACE(14);
            }
        }
        return;
    }

    asm volatile("setmaxnreg.inc.sync.aligned.u32 168;");
    const int g = lane >> 2, t = lane & 3;
    const int ks0 = warp < 4 ? 5 * warp : 20 + 4 * (warp - 4);
    const int nks = warp < 4 ? 5 : 4;
    const int lk = (lane & 7) + 8 * (lane >> 4);
    const int mh = (lane >> 3) & 1;
    const uint32_t bfrag = misc + OFF_ACT + ((g & 3) * APITCH + 2 * t) * 2;
    asm volatile("bar.sync 2, 288;" ::: "memory");
    const uint32_t ntag = epoch & 1u, tag = ntag ^ 1u;
    if (tune.prewrite0 && tid < 128) {
        st_rlx32(&g_q[(tid >> 5) * HQD + 32 * cta + lane], ntag);
        if (has_mod) st_rlx32(&g_mod[(tid >> 5) * N_MOD + 32 * modb + lane], ntag);
    }

#pragma unroll 1
    for (int ph = 0; ph < 2; ph++) {
        asm volatile("bar.sync %0, 384;" :: "r"(3 + ph) : "memory");
        const bool active = ph == 1 || has_mod;
        if (active) {
            mbar_wait(bar(B_MOD + ph), 0);
            float acc[2][4] = {};
#pragma unroll 1
            for (int s = 0; s < nks; s++) {
                const int ks = ks0 + s;
                const uint32_t b0 = lds32(bfrag + ks * 32), b1 = lds32(bfrag + ks * 32 + 16);
                const int k = ks * 16 + lk;
                const uint32_t rowa = sbase + PRO_OFF + ph * 36864 + k * 64;
#pragma unroll
                for (int j = 0; j < 2; j++) {
                    uint32_t a[4];
                    ldsm4t(a, rowa + (((2 * j + mh) ^ ((k >> 1) & 3)) << 4));
                    mma16816(acc[j], a, b0, b1);
                }
            }
            if (t < 2) {
#pragma unroll
                for (int j = 0; j < 2; j++) {
                    *reinterpret_cast<float2*>(red + warp * 128 + (16 * j + g) * 4 + 2 * t) = make_float2(acc[j][0], acc[j][1]);
                    *reinterpret_cast<float2*>(red + warp * 128 + (16 * j + g + 8) * 4 + 2 * t) = make_float2(acc[j][2], acc[j][3]);
                }
            }
        }
        if (ph == 0) asm volatile("bar.arrive 6, 384;" ::: "memory");
        else { __syncwarp(); if (lane == 0) mbar_arrive(bar(B_PROFREE)); }
        cbar();
        if (active && tid < 128) {
            const int b = tid >> 5;
            float s = 0.f;
#pragma unroll
            for (int w = 0; w < 8; w++) s += red[w * 128 + lane * 4 + b];
            unsigned* dst = ph == 0 ? &g_mod[b * N_MOD + 32 * modb] : &g_q[b * HQD + 32 * cta];
            st_rlx32(dst + lane, (pack_bf2(0.f, s) & 0xffff0000u) | tag);
        }
        if (tid == 0) TRACE(3 + ph);
    }
    {
        const unsigned* p = &g_q[((cta >> 1) & 3) * HQD + (cta >> 3) * 256 + tid];
        uint32_t w;
        int it = 0;
#pragma unroll 1
        do { w = ld_rlx32(p); if (++it > SPIN_LIMIT) __trap(); } while ((w & 1u) != tag);
        reinterpret_cast<unsigned short*>(sgen + RING + OFF_Q)[(tid >> 7) * 136 + (tid & 127)] = (unsigned short)(w >> 16);
    }
    cbar();
    uint32_t qf[8][2];
#pragma unroll
    for (int ks = 0; ks < 8; ks++) {
        const uint32_t a = misc + OFF_Q + ((g & 1) * 136 + ks * 16 + 2 * t) * 2;
        qf[ks][0] = lds32(a); qf[ks][1] = lds32(a + 16);
    }
    if (tid == 0) TRACE(5);

    {
        const float SCALE = 0.08838834764831845f;
        float o[8][4];
#pragma unroll
        for (int j = 0; j < 8; j++) { o[j][0] = o[j][1] = o[j][2] = o[j][3] = 0.f; }
        float m0 = -INFINITY, m1 = -INFINITY, l0 = 0.f, l1 = 0.f;
        const int wr = (warp & 3) * 16;
        const int krow = wr + (lane & 7) + 8 * ((lane >> 3) & 1);
        const int kch = lane >> 4;
        const int vrow = wr + lk;
#pragma unroll 1
        for (int j = warp >> 2; j < 32; j += 2) {
            const uint32_t ik = tune.slot[2 * j], iv = tune.slot[2 * j + 1];
            const uint32_t sk = ik & 15u, uk = ik >> 4, sv = iv & 15u, uv = iv >> 4;
            if ((j | 1) == tune.prewrite) {
                if ((tid & 3) == 0) st_rlx64(&g_o[cta * 72 + (tid >> 2)], ntag);
                if (tid < 4) st_rlx64(&g_o[cta * 72 + 64 + tid], ntag);
                if (is_wo && tid < 64) st_rlx32(&g_y[((wou & 1) * 4 + (tid >> 4)) * D_MODEL + 16 * (wou >> 1) + (tid & 15)], ntag);
            }
            mbar_wait(bar(B_FULL + sk), uk & 1);
            const uint32_t kb = sbase + sk * SLOT + krow * 128;
            float sa[4] = {0.f, 0.f, 0.f, 0.f}, sb[4] = {0.f, 0.f, 0.f, 0.f};
#pragma unroll
            for (int ks = 0; ks < 4; ks++) {
                uint32_t a[4], a2[4];
                ldsm4(a, kb + (((2 * ks + kch) ^ (krow & 7)) << 4));
                ldsm4(a2, kb + 8192 + (((2 * ks + kch) ^ (krow & 7)) << 4));
                mma16816(sa, a, qf[ks][0], qf[ks][1]);
                mma16816(sb, a2, qf[ks + 4][0], qf[ks + 4][1]);
            }
            __syncwarp();
            if (lane == 0) mbar_arrive(bar(B_EMPTY + sk));
            float s[4];
            {
                const uint32_t r01 = pack_bf2(sa[0] + sb[0], sa[1] + sb[1]), r23 = pack_bf2(sa[2] + sb[2], sa[3] + sb[3]);
                const uint32_t u01 = pack_bf2(bf_lo(r01) * SCALE, bf_hi(r01) * SCALE), u23 = pack_bf2(bf_lo(r23) * SCALE, bf_hi(r23) * SCALE);
                s[0] = bf_lo(u01); s[1] = bf_hi(u01); s[2] = bf_lo(u23); s[3] = bf_hi(u23);
            }
            float x0 = fmaxf(s[0], s[2]), x1 = fmaxf(s[1], s[3]);
#pragma unroll
            for (int of = 4; of < 32; of <<= 1) {
                x0 = fmaxf(x0, __shfl_xor_sync(0xffffffffu, x0, of));
                x1 = fmaxf(x1, __shfl_xor_sync(0xffffffffu, x1, of));
            }
            if (x0 > m0 || x1 > m1) {
                const float n0 = fmaxf(m0, x0), n1 = fmaxf(m1, x1);
                const float f0 = ex2((m0 - n0) * LOG2E), f1 = ex2((m1 - n1) * LOG2E);
                m0 = n0; m1 = n1; l0 *= f0; l1 *= f1;
#pragma unroll
                for (int jj = 0; jj < 8; jj++) { o[jj][0] *= f0; o[jj][1] *= f1; o[jj][2] *= f0; o[jj][3] *= f1; }
            }
            const float p0 = ex2((s[0] - m0) * LOG2E), p1 = ex2((s[1] - m1) * LOG2E);
            const float p2 = ex2((s[2] - m0) * LOG2E), p3 = ex2((s[3] - m1) * LOG2E);
            l0 += p0 + p2; l1 += p1 + p3;
            const uint32_t pb0 = movtrans(pack_bf2(p0, p1)), pb1 = movtrans(pack_bf2(p2, p3));
            mbar_wait(bar(B_FULL + sv), uv & 1);
            const uint32_t vb = sbase + sv * SLOT + vrow * 128;
#pragma unroll
            for (int dt = 0; dt < 8; dt++) {
                uint32_t a[4];
                ldsm4t(a, vb + (dt >> 2) * 8192 + (((2 * (dt & 3) + mh) ^ (vrow & 7)) << 4));
                mma16816(o[dt], a, pb0, pb1);
            }
            __syncwarp();
            if (lane == 0) mbar_arrive(bar(B_EMPTY + sv));
        }
        if (tid == 0) TRACE(6);
#pragma unroll
        for (int of = 4; of < 32; of <<= 1) {
            l0 += __shfl_xor_sync(0xffffffffu, l0, of);
            l1 += __shfl_xor_sync(0xffffffffu, l1, of);
        }
        float* rw = red + warp * 264;
        if (t < 2) {
#pragma unroll
            for (int dt = 0; dt < 8; dt++) {
                rw[128 * t + 16 * dt + g] = t ? o[dt][1] : o[dt][0];
                rw[128 * t + 16 * dt + g + 8] = t ? o[dt][3] : o[dt][2];
            }
            if (g == 0) { rw[256 + t] = t ? m1 : m0; rw[258 + t] = t ? l1 : l0; }
        }
    }
    cbar();
    {
        const int word = tid >> 2, e = tid & 3;
        const int k = (2 * (word >> 3) + (word & 1)) * 16 + 2 * ((word >> 1) & 3) + (e & 1) + 8 * (e >> 1);
        const int hd = tid >> 7;
        float mw[8];
        float M = -INFINITY;
#pragma unroll
        for (int w = 0; w < 8; w++) { mw[w] = red[w * 264 + 256 + hd]; M = fmaxf(M, mw[w]); }
        float L = 0.f, acc = 0.f;
#pragma unroll
        for (int w = 0; w < 8; w++) {
            const float f = ex2((mw[w] - M) * LOG2E);
            L = fmaf(f, red[w * 264 + 258 + hd], L);
            acc = fmaf(f, red[w * 264 + k], acc);
        }
        const float val = __fdividef(acc, L);
        uint32_t u = __float_as_uint(val);
        const uint32_t hb = e == 0 ? ((((u + 0xffffu + ((u >> 17) & 1u)) >> 16) & 0xfffeu) | tag) : (pack_bf2(val, 0.f) & 0xffffu);
        const uint32_t pr = hb | (__shfl_down_sync(0xffffffffu, hb, 1) << 16);
        const uint32_t p2 = __shfl_down_sync(0xffffffffu, pr, 2);
        if (e == 0) st_rlx64(&g_o[cta * 72 + word], (unsigned long long)pr | ((unsigned long long)p2 << 32));
        if ((tid & 127) == 0) st_rlx64(&g_o[cta * 72 + 64 + hd], (unsigned long long)tagf(L, tag) | ((unsigned long long)__float_as_uint(M) << 32));
    }
    asm volatile("bar.arrive 7, 384;" ::: "memory");
    if (tid == 0) TRACE(7);

    if (is_wo) {
        const int prod0 = (8 * (wou & 1) + warp) * 8;
        const unsigned long long* po = &g_o[(prod0 + g) * 72 + 2 * t];
        const unsigned long long* pm = &g_o[(prod0 + 2 * t) * 72 + 64];
        mbar_wait(bar(B_WO + (warp >> 1)), 0);
        if (tid == 0) TRACE(23);
        uint32_t wa[16][4];
        const uint32_t wb = sbase + warp * 8192 + lk * 32 + ((mh ^ ((lk >> 2) & 1)) << 4);
#pragma unroll
        for (int i = 0; i < 16; i++) ldsm4t(wa[i], wb + i * 512);
        uint4 ob[10];
        {
            int it = 0;
#pragma unroll 1
            while (true) {
                const unsigned long long w = ld_rlx64(&g_o[(prod0 + g) * 72 + 64]);
                if (__popc(__ballot_sync(0xffffffffu, (((uint32_t)w ^ tag) & 1u) != 0u)) <= 8) break;
                if (++it > SPIN_LIMIT) __trap();
            }
        }
        gather128<10, true>(ob, [&](int i) { return i < 8 ? po + 8 * i : pm + (i - 8) * 72; }, tag);
        __syncwarp();
        if (tid == 0) TRACE(8);
        float acc[4][4] = {};
#pragma unroll
        for (int i = 0; i < 8; i++) {
            mma16816(acc[(i >> 2) * 2], wa[2 * i], ob[i].x & ~1u, ob[i].y);
            mma16816(acc[(i >> 2) * 2 + 1], wa[2 * i + 1], ob[i].z & ~1u, ob[i].w);
        }
        float y0 = 0.f, y1 = 0.f;
#pragma unroll
        for (int hd = 0; hd < 2; hd++) {
            const float la = __uint_as_float(hd ? ob[8].z : ob[8].x), ma = __uint_as_float(hd ? ob[8].w : ob[8].y);
            const float lb = __uint_as_float(hd ? ob[9].z : ob[9].x), mb = __uint_as_float(hd ? ob[9].w : ob[9].y);
            const float M = fmaxf(ma, mb);
            float fa = la * ex2((ma - M) * LOG2E), fb = lb * ex2((mb - M) * LOG2E);
            const float inv = __fdividef(1.0f, fa + fb);
            fa *= inv; fb *= inv;
            y0 += fa * (acc[2 * hd][0] + acc[2 * hd + 1][0]) + fb * (acc[2 * hd][1] + acc[2 * hd + 1][1]);
            y1 += fa * (acc[2 * hd][2] + acc[2 * hd + 1][2]) + fb * (acc[2 * hd][3] + acc[2 * hd + 1][3]);
        }
        float* r2 = red + 2112;
        r2[warp * 64 + t * 16 + g] = y0;
        r2[warp * 64 + t * 16 + g + 8] = y1;
        cbar();
        if (tid < 64) {
            float s = 0.f;
#pragma unroll
            for (int w = 0; w < 8; w++) s += r2[w * 64 + tid];
            st_rlx32(&g_y[((wou & 1) * 4 + (tid >> 4)) * D_MODEL + 16 * (wou >> 1) + (tid & 15)], tagf(s, tag));
        }
        if (tid == 0) TRACE(9);
    }

    {
        const uint32_t pitch = fw * 2, swz = wide ? 0u : 3u;
        uint32_t ga[5][5][4];
        const uint32_t x = (lk >> 1) & swz;
#pragma unroll 1
        for (int i = 2 * (ks0 / 12); i < 2 * ((ks0 + nks - 1) / 12) + 2; i++) mbar_wait(bar(B_GU + i), 0);
#pragma unroll
        for (int s = 0; s < 5; s++) if (s < nks) {
            const int ks = ks0 + s, bx = ks / 12;
            const uint32_t ra = sbase + gu_off + (2 * bx + mh) * boxb + ((ks - 12 * bx) * 16 + lk) * pitch;
#pragma unroll
            for (int j = 0; j < 5; j++) if (j < 4 || wide) ldsm4t(ga[s][j], ra + ((j ^ x) << 4));
        }
        if (tid == 224) TRACE(11);
        asm volatile("bar.sync 5, 384;" ::: "memory");
        float acc[5][4] = {};
#pragma unroll
        for (int s = 0; s < 5; s++) if (s < nks) {
            const uint32_t b0 = lds32(bfrag + (ks0 + s) * 32), b1 = lds32(bfrag + (ks0 + s) * 32 + 16);
#pragma unroll
            for (int j = 0; j < 5; j++) if (j < 4 || wide) mma16816(acc[j], ga[s][j], b0, b1);
        }
        if (t < 2) {
#pragma unroll
            for (int j = 0; j < 5; j++) if (j < 4 || wide) {
                *reinterpret_cast<float2*>(red + warp * 320 + (16 * j + g) * 4 + 2 * t) = make_float2(acc[j][0], acc[j][1]);
                *reinterpret_cast<float2*>(red + warp * 320 + (16 * j + g + 8) * 4 + 2 * t) = make_float2(acc[j][2], acc[j][3]);
            }
        }
        cbar();
        if (tid < fw * 4) {
            float gs = 0.f, us = 0.f;
#pragma unroll
            for (int w = 0; w < 8; w++) { gs += red[w * 320 + warp * 64 + lane]; us += red[w * 320 + warp * 64 + 32 + lane]; }
            gs = bfr(gs); us = bfr(us);
            const float u2 = (-2.0f * 0.7978845608028654f * LOG2E) * (gs + 0.044715f * gs * gs * gs);
            const float ge = bfr(__fdividef(gs, 1.0f + ex2(u2)));
            reinterpret_cast<__nv_bfloat16*>(sgen + RING + OFF_A2)[t * 48 + 8 * warp + g] = __float2bfloat16_rn(ge * us);
        }
        cbar();
    }
    if (tid == 0) TRACE(24);
    {
        const uint32_t af = misc + OFF_A2 + ((g & 3) * 48 + 2 * t) * 2;
        const uint32_t b00 = lds32(af), b01 = lds32(af + 16), b10 = lds32(af + 32), b11 = lds32(af + 48);
        const uint32_t b2 = lds32(af + 64);
        const int cc = 2 * warp + mh;
        const uint32_t db8 = sbase + dn_off + (cc >> 3) * 1024 + (lane & 7) * 128 + (((cc & 7) ^ (lane & 7)) << 4);
        const uint32_t db = db8 + (lane >> 4) * 9216;
        unsigned* dst = &g_d[(2 * warp * NCTA + cta) * 32 + g * 4 + 2 * t];
        uint32_t a[5][4], a2[5][4], a3[5][2];
        float acc[5][4] = {};
        mbar_wait(bar(B_DN), 0);
#pragma unroll
        for (int jj = 0; jj < 5; jj++) if (jj < 4 || warp < 4) ldsm4t(a[jj], db + jj * 2048);
        mbar_wait(bar(B_DN + 1), 0);
#pragma unroll
        for (int jj = 0; jj < 5; jj++) if (jj < 4 || warp < 4) ldsm4t(a2[jj], db + 18432 + jj * 2048);
        if (wide) {
            mbar_wait(bar(B_DN + 2), 0);
#pragma unroll
            for (int jj = 0; jj < 5; jj++) if (jj < 4 || warp < 4) ldsm2t(a3[jj], db8 + 36864 + jj * 2048);
        }
        if (tid == 0) TRACE(12);
#pragma unroll
        for (int jj = 0; jj < 5; jj++) if (jj < 4 || warp < 4) mma16816(acc[jj], a[jj], b00, b01);
#pragma unroll
        for (int jj = 0; jj < 5; jj++) if (jj < 4 || warp < 4) mma16816(acc[jj], a2[jj], b10, b11);
        if (wide) {
#pragma unroll
            for (int jj = 0; jj < 5; jj++) if (jj < 4 || warp < 4) mma1688(acc[jj], a3[jj], b2);
        }
        if (t < 2) {
#pragma unroll
            for (int jj = 0; jj < 5; jj++) if (jj < 4 || warp < 4) {
                st_rlx2x32(dst + jj * 16 * NCTA * 32, tagf(acc[jj][0], tag), tagf(acc[jj][1], tag));
                st_rlx2x32(dst + (jj * 16 + 1) * NCTA * 32, tagf(acc[jj][2], tag), tagf(acc[jj][3], tag));
            }
        }
    }
    if (rid >= 0) asm volatile("bar.arrive 8, 384;" ::: "memory");
    if (tid == 0) TRACE(13);
}

typedef CUresult (*EncodeFn)(CUtensorMap*, CUtensorMapDataType, cuuint32_t, void*, const cuuint64_t*, const cuuint64_t*,
                             const cuuint32_t*, const cuuint32_t*, CUtensorMapInterleave, CUtensorMapSwizzle,
                             CUtensorMapL2promotion, CUtensorMapFloatOOBfill);

void make2d(EncodeFn enc, CUtensorMap* m, const void* base, int rows, int cols, int boxc, int boxr, CUtensorMapSwizzle sw) {
    cuuint64_t dims[2] = {(cuuint64_t)cols, (cuuint64_t)rows};
    cuuint64_t str[1] = {(cuuint64_t)cols * 2};
    cuuint32_t box[2] = {(cuuint32_t)boxc, (cuuint32_t)boxr};
    cuuint32_t es[2] = {1, 1};
    enc(m, CU_TENSOR_MAP_DATA_TYPE_BFLOAT16, 2, const_cast<void*>(base), dims, str, box, es, CU_TENSOR_MAP_INTERLEAVE_NONE, sw,
        CU_TENSOR_MAP_L2_PROMOTION_L2_256B, CU_TENSOR_MAP_FLOAT_OOB_FILL_NONE);
}
void make3d(EncodeFn enc, CUtensorMap* m, const void* base, int rows, int chunks, int boxr) {
    cuuint64_t dims[3] = {64, (cuuint64_t)rows, (cuuint64_t)chunks};
    cuuint64_t str[2] = {(cuuint64_t)chunks * 128, 128};
    cuuint32_t box[3] = {64, (cuuint32_t)boxr, (cuuint32_t)chunks};
    cuuint32_t es[3] = {1, 1, 1};
    enc(m, CU_TENSOR_MAP_DATA_TYPE_BFLOAT16, 3, const_cast<void*>(base), dims, str, box, es, CU_TENSOR_MAP_INTERLEAVE_NONE,
        CU_TENSOR_MAP_SWIZZLE_128B, CU_TENSOR_MAP_L2_PROMOTION_L2_256B, CU_TENSOR_MAP_FLOAT_OOB_FILL_NONE);
}

struct Tune {
    float rate;
    float lead;
    int early_slots;
    int early_ops[3];
    int cap_late[3];
    int cap_start, cap_main, cap_tail;
    int n_start;
    int sw_tail;
    int prewrite;
};
Tune g_tune = {3200.f, 2.f, 2, {2, 0, 2}, {3, 3, 4}, 4, 5, 3, 8, 60, 329};

void build_sched(const Tune& t, Sched& sc) {
    const int E = t.early_slots, A = 51 + E;
    int uses[NSLOT] = {0}, useidx[NKV];
    int rounds = (A - 26 + NSLOT - 1) / NSLOT, skip = rounds * NSLOT - (A - 26);
    int i = 0;
    auto put = [&](int s) { sc.slot[i] = (unsigned char)(s | ((uses[s] & 1) << 4)); useidx[i] = uses[s]; i++; uses[s]++; };
    for (int r = 0; r < 2; r++) for (int s = 0; s < NSLOT; s++) put(s);
    for (int r = 0; r < rounds; r++) {
        const int sk = (skip + (rounds - r) - 1) / (rounds - r);
        skip -= sk;
        for (int s = sk; s < NSLOT; s++) put(s);
    }
    for (int s = E; s < NSLOT; s++) put(s);
    sc.prewrite = t.prewrite % 100; sc.prewrite0 = (t.prewrite / 100) & 1; sc.prewrite2 = (t.prewrite / 200) & 1;
    int toff[3][13], tlen[3][13], tfirst[3], tcnt[3], ne[3];
    double early_bytes = 0;
    for (int c = 0; c < 3; c++) {
        const bool wide = c > 0, wo = c != 1;
        const int boxb = 192 * (wide ? 40 : 32) * 2, gu = wo ? 65536 : 0;
        for (int tj = 0; tj < 13; tj++) {
            toff[c][tj] = tj < 4 ? tj * 16384 : (tj < 10 ? gu + (tj - 4) * boxb : gu + 6 * boxb + (tj - 10) * 18432);
            tlen[c][tj] = tj < 4 ? 16384 : (tj < 10 ? boxb : (tj < 12 ? 18432 : 9216));
        }
        tfirst[c] = wo ? 0 : 4;
        tcnt[c] = (wide ? 13 : 12) - tfirst[c];
        ne[c] = 0;
        while (ne[c] < t.early_ops[c] && ne[c] < tcnt[c] && toff[c][tfirst[c] + ne[c]] + tlen[c][tfirst[c] + ne[c]] <= E * SLOT) {
            early_bytes += (c == 0 ? 64 : (c == 1 ? 56 : 8)) * (double)tlen[c][tfirst[c] + ne[c]];
            ne[c]++;
        }
    }
    const double pro_bytes = 576.0 * (N_MOD + HQD) * 2, tile_bytes = (double)SLOT * NCTA;
    for (int c = 0; c < 3; c++) {
        const int n = NKV + tcnt[c];
        sc.nops[c] = n;
        int code[MAXOPS + 4];
        code[0] = code[1] = B_MOD; code[2] = code[3] = B_WQ;
        for (int m = 0; m < MAXOPS; m++) {
            if (m >= n) { sc.ops[c][m] = make_uint2(0u, 0u); continue; }
            int kv = -1, tl = -1;
            if (m < A) kv = m; else if (m < A + ne[c]) tl = m - A; else if (m < NKV + ne[c]) kv = m - ne[c]; else tl = m - NKV;
            int wa = 127, wb = 127, full, dst, op, cap;
            double bytes_before;
            if (kv >= 0) {
                const int s = sc.slot[kv] & 15, u = useidx[kv];
                if (kv == 8) wa = B_PROFREE;
                if (u > 0) wa = (B_EMPTY + s) | (((u - 1) & 1) << 7);
                full = (B_FULL + s) | ((u & 1) << 7);
                dst = s * 16; op = kv;
                cap = kv < t.n_start ? t.cap_start : (kv < t.sw_tail ? t.cap_main : t.cap_tail);
                bytes_before = pro_bytes + (kv - t.lead) * tile_bytes + (kv >= A ? early_bytes : 0.0);
            } else {
                const int tj = tfirst[c] + tl, last = (toff[c][tj] + tlen[c][tj] - 1) / SLOT;
                wa = (B_EMPTY + last) | (((uses[last] - 1) & 1) << 7);
                if (last > 0) wb = (B_EMPTY + last - 1) | (((uses[last - 1] - 1) & 1) << 7);
                full = B_WO + tj;
                dst = toff[c][tj] / 1024; op = 64 + tj;
                cap = tl < ne[c] ? (A < t.sw_tail ? t.cap_main : t.cap_tail) : t.cap_late[c];
                bytes_before = tl < ne[c] ? pro_bytes + (A - t.lead) * tile_bytes + early_bytes * tl / ne[c] : 0.0;
            }
            code[m + 4] = full;
            const int wc = m + 4 - cap >= 0 ? code[m + 4 - cap] : 127;
            int tmin = t.rate > 0.f && bytes_before > 0.0 ? (int)(bytes_before / t.rate) : 0;
            if (tmin > 65535) tmin = 65535;
            sc.ops[c][m] = make_uint2((unsigned)wa | ((unsigned)wb << 8) | ((unsigned)wc << 16) | ((unsigned)full << 24),
                                      (unsigned)dst | ((unsigned)op << 8) | ((unsigned)tmin << 16));
        }
    }
}

}

extern "C" void kernel_launch(void* const* d_in, const int* in_sizes, int n_in, void* d_out, int out_size) {
    (void)in_sizes; (void)n_in; (void)out_size;
    static EncodeFn enc = nullptr;
    if (!enc) {
        void* fn = nullptr;
        cudaDriverEntryPointQueryResult qr;
        cudaGetDriverEntryPoint("cuTensorMapEncodeTiled", &fn, cudaEnableDefault, &qr);
        enc = (EncodeFn)fn;
        cudaFuncSetAttribute(fused_decode_kernel, cudaFuncAttributeMaxDynamicSharedMemorySize, SMEM_BYTES);
    }
    Sched sched;
    build_sched(g_tune, sched);
    Maps maps;
    make3d(enc, &maps.k, d_in[1], 262144, 2, 64);
    make3d(enc, &maps.v, d_in[2], 262144, 2, 64);
    make3d(enc, &maps.wd, d_in[8], FF, 9, 8);
    make2d(enc, &maps.wmod, d_in[10], D_MODEL, N_MOD, 32, 192, CU_TENSOR_MAP_SWIZZLE_64B);
    make2d(enc, &maps.wq, d_in[3], D_MODEL, HQD, 32, 192, CU_TENSOR_MAP_SWIZZLE_64B);
    make2d(enc, &maps.wo, d_in[4], HQD, D_MODEL, 16, 256, CU_TENSOR_MAP_SWIZZLE_32B);
    make2d(enc, &maps.g32, d_in[6], D_MODEL, FF, 32, 192, CU_TENSOR_MAP_SWIZZLE_64B);
    make2d(enc, &maps.u32, d_in[7], D_MODEL, FF, 32, 192, CU_TENSOR_MAP_SWIZZLE_64B);
    make2d(enc, &maps.g40, d_in[6], D_MODEL, FF, 40, 192, CU_TENSOR_MAP_SWIZZLE_NONE);
    make2d(enc, &maps.u40, d_in[7], D_MODEL, FF, 40, 192, CU_TENSOR_MAP_SWIZZLE_NONE);
    fused_decode_kernel<<<NCTA, NTHREADS, SMEM_BYTES>>>(maps, sched, (const __nv_bfloat16*)d_in[0], (const __nv_bfloat16*)d_in[9],
                                                        (__nv_bfloat16*)d_out);
}
```

```cpp
#include <cuda_runtime.h>
#include <cuda_bf16.h>
#include <cuda.h>
#include <stdint.h>

namespace {

constexpr int D_MODEL = 576;
constexpr int N_MOD = 6 * D_MODEL;
constexpr int HQD = 4096;
constexpr int FF = 4608;
constexpr int NCTA = 132;
constexpr int NF = 96;
constexpr int NW = 36;
constexpr int NTHREADS = 512;
constexpr int NSLOT = 13;
constexpr int SLOT = 16384;
constexpr int RING = NSLOT * SLOT;
constexpr int NKV = 64;
constexpr int NSW = 27;
constexpr int PER = 2 * NSW;
constexpr int APITCH = 584;
constexpr int PRO_OFF = 8 * SLOT;
constexpr int FOP = 18432;
constexpr int SILU_OFF = 12 * SLOT + 8192;

constexpr int OFF_BAR = 0;
constexpr int OFF_CTL = 448;
constexpr int OFF_ACT = 512;
constexpr int OFF_RED = OFF_ACT + 4672;
constexpr int OFF_ML = OFF_RED + 12288;
constexpr int OFF_Q = OFF_ML + 128;
constexpr int OFF_TAB = OFF_Q + 576;
constexpr int MISC = OFF_TAB + 640;
constexpr int SMEM_BYTES = RING + MISC;

constexpr int B_FULL = 0, B_EMPTY = 13, B_P1 = 26, B_P2 = 27, B_PROFREE = 28, B_ML = 29, B_T = 30  , B_COUNT = 39;

struct Maps {
    CUtensorMap k, v, wmod, wq, wo, g32, u32, g16, u16, wd, wm16;
};
constexpr int MAXOPS = 72;
constexpr int NPRE = 8;
struct Sched {
    uint2 ops[3][MAXOPS];
    unsigned char slot[2][NKV];
};
struct Hot {
    unsigned wo_slots;
    int g_kv0;
    int g_pw, g_x;
    int poll_gap, thr_y, thr_d;
    int n_timed, t_kv0, dt_kv;
};

constexpr int NREP = 2;
struct Scratch {
    unsigned d[NW * NF * 64];
    unsigned long long o[16 * 512];
    unsigned long long ml[128 * 4];
    uint4 part[64 * PER * 32];
    uint4 pml[64 * PER * 2];
    unsigned mod[4 * N_MOD];
    unsigned q[4 * HQD];
    unsigned y[2 * 4 * D_MODEL];
    unsigned cnt[NREP][64];
    unsigned epoch;
};
constexpr unsigned TOTAL_KB = 159728;
__device__ __align__(1024) Scratch g_scratch;

constexpr int SPIN_LIMIT = 1 << 22;

__device__ __forceinline__ uint32_t clk32() { uint32_t t; asm volatile("mov.u32 %0, %%clock;" : "=r"(t)); return t; }
__device__ __forceinline__ uint32_t smem_u32(const void* p) { return (uint32_t)__cvta_generic_to_shared(p); }
__device__ __forceinline__ void mbar_init(uint32_t bar, uint32_t cnt) { asm volatile("mbarrier.init.shared::cta.b64 [%0], %1;" :: "r"(bar), "r"(cnt) : "memory"); }
__device__ __forceinline__ void mbar_expect_tx(uint32_t bar, uint32_t bytes) { asm volatile("mbarrier.arrive.expect_tx.shared::cta.b64 _, [%0], %1;" :: "r"(bar), "r"(bytes) : "memory"); }
__device__ __forceinline__ void mbar_arrive(uint32_t bar) { asm volatile("mbarrier.arrive.shared::cta.b64 _, [%0];" :: "r"(bar) : "memory"); }
__device__ __forceinline__ bool mbar_try_wait(uint32_t bar, uint32_t parity) {
    uint32_t ok;
    asm volatile("{\n.reg .pred p;\nmbarrier.try_wait.parity.shared::cta.b64 p, [%1], %2;\nselp.u32 %0, 1, 0, p;\n}" : "=r"(ok) : "r"(bar), "r"(parity) : "memory");
    return ok;
}
__device__ __forceinline__ bool mbar_test(uint32_t bar, uint32_t parity) {
    uint32_t ok;
    asm volatile("{\n.reg .pred p;\nmbarrier.test_wait.parity.shared::cta.b64 p, [%1], %2;\nselp.u32 %0, 1, 0, p;\n}" : "=r"(ok) : "r"(bar), "r"(parity) : "memory");
    return ok;
}
__device__ __forceinline__ void mbar_wait(uint32_t bar, uint32_t parity) {
    int it = 0;
#pragma unroll 1
    while (!mbar_try_wait(bar, parity)) { if (++it > SPIN_LIMIT) __trap(); }
}
__device__ __forceinline__ uint64_t policy_stream() {
    uint64_t p; asm volatile("createpolicy.fractional.L2::evict_first.b64 %0, 1.0;" : "=l"(p)); return p;
}
__device__ __forceinline__ void tma2d(uint32_t dst, const CUtensorMap* m, int c0, int c1, uint32_t bar) {
    asm volatile("cp.async.bulk.tensor.2d.shared::cluster.global.mbarrier::complete_tx::bytes [%0], [%1, {%3, %4}], [%2];" :: "r"(dst), "l"(m), "r"(bar), "r"(c0), "r"(c1) : "memory");
}
__device__ __forceinline__ void tma2dh(uint32_t dst, const CUtensorMap* m, int c0, int c1, uint32_t bar, uint64_t pol) {
    asm volatile("cp.async.bulk.tensor.2d.shared::cluster.global.mbarrier::complete_tx::bytes.L2::cache_hint [%0], [%1, {%3, %4}], [%2], %5;" :: "r"(dst), "l"(m), "r"(bar), "r"(c0), "r"(c1), "l"(pol) : "memory");
}
__device__ __forceinline__ void tma3d(uint32_t dst, const CUtensorMap* m, int c0, int c1, int c2, uint32_t bar, uint64_t pol) {
    asm volatile("cp.async.bulk.tensor.3d.shared::cluster.global.mbarrier::complete_tx::bytes.L2::cache_hint [%0], [%1, {%3, %4, %5}], [%2], %6;"
                 :: "r"(dst), "l"(m), "r"(bar), "r"(c0), "r"(c1), "r"(c2), "l"(pol) : "memory");
}
__device__ __forceinline__ void ldsm4(uint32_t (&r)[4], uint32_t addr) {
    asm volatile("ldmatrix.sync.aligned.m8n8.x4.shared.b16 {%0,%1,%2,%3}, [%4];" : "=r"(r[0]), "=r"(r[1]), "=r"(r[2]), "=r"(r[3]) : "r"(addr) : "memory");
}
__device__ __forceinline__ void ldsm4t(uint32_t (&r)[4], uint32_t addr) {
    asm volatile("ldmatrix.sync.aligned.m8n8.x4.trans.shared.b16 {%0,%1,%2,%3}, [%4];" : "=r"(r[0]), "=r"(r[1]), "=r"(r[2]), "=r"(r[3]) : "r"(addr) : "memory");
}
__device__ __forceinline__ void mma16816(float (&c)[4], const uint32_t (&a)[4], uint32_t b0, uint32_t b1) {
    asm volatile("mma.sync.aligned.m16n8k16.row.col.f32.bf16.bf16.f32 {%0,%1,%2,%3}, {%4,%5,%6,%7}, {%8,%9}, {%0,%1,%2,%3};"
                 : "+f"(c[0]), "+f"(c[1]), "+f"(c[2]), "+f"(c[3]) : "r"(a[0]), "r"(a[1]), "r"(a[2]), "r"(a[3]), "r"(b0), "r"(b1));
}
__device__ __forceinline__ uint32_t movtrans(uint32_t a) {
    uint32_t d; asm volatile("movmatrix.sync.aligned.m8n8.trans.b16 %0, %1;" : "=r"(d) : "r"(a)); return d;
}
__device__ __forceinline__ uint32_t lds32(uint32_t addr) { uint32_t v; asm volatile("ld.shared.b32 %0, [%1];" : "=r"(v) : "r"(addr) : "memory"); return v; }
__device__ __forceinline__ void cbar() { asm volatile("bar.sync 1, 256;" ::: "memory"); }

__device__ __forceinline__ uint32_t pack_bf2(float lo, float hi) {
    uint32_t r; asm("cvt.rn.bf16x2.f32 %0, %1, %2;" : "=r"(r) : "f"(hi), "f"(lo)); return r;
}
__device__ __forceinline__ uint32_t bmul2(uint32_t a, uint32_t b) { uint32_t r; asm("mul.rn.bf16x2 %0, %1, %2;" : "=r"(r) : "r"(a), "r"(b)); return r; }
__device__ __forceinline__ uint32_t badd2(uint32_t a, uint32_t b) { uint32_t r; asm("add.rn.bf16x2 %0, %1, %2;" : "=r"(r) : "r"(a), "r"(b)); return r; }
__device__ __forceinline__ uint32_t bsub2(uint32_t a, uint32_t b) { uint32_t r; asm("sub.rn.bf16x2 %0, %1, %2;" : "=r"(r) : "r"(a), "r"(b)); return r; }
__device__ __forceinline__ float bf_lo(uint32_t w) { return __uint_as_float(w << 16); }
__device__ __forceinline__ float bf_hi(uint32_t w) { return __uint_as_float(w & 0xffff0000u); }

__device__ __forceinline__ float bfr(float x) { return __uint_as_float(pack_bf2(0.f, x)); }
__device__ __forceinline__ uint32_t ld_rlx32(const void* p) { uint32_t v; asm volatile("ld.relaxed.gpu.global.b32 %0, [%1];" : "=r"(v) : "l"(p) : "memory"); return v; }
__device__ __forceinline__ uint4 ld_rlx128(const void* p) {
    uint4 v; asm volatile("ld.relaxed.gpu.global.v4.b32 {%0,%1,%2,%3}, [%4];" : "=r"(v.x), "=r"(v.y), "=r"(v.z), "=r"(v.w) : "l"(p) : "memory"); return v;
}
__device__ __forceinline__ uint4 ld_rlx2x64(const void* p) {
    uint4 v;
    asm volatile("{\n.reg .b64 a, b;\nld.relaxed.gpu.global.v2.b64 {a, b}, [%4];\nmov.b64 {%0,%1}, a;\nmov.b64 {%2,%3}, b;\n}"
                 : "=r"(v.x), "=r"(v.y), "=r"(v.z), "=r"(v.w) : "l"(p) : "memory");
    return v;
}
__device__ __forceinline__ float ex2(float x) { float r; asm("ex2.approx.ftz.f32 %0, %1;" : "=f"(r) : "f"(x)); return r; }
__device__ __forceinline__ void st_rlx32(void* p, uint32_t v) { asm volatile("st.relaxed.gpu.global.b32 [%0], %1;" :: "l"(p), "r"(v) : "memory"); }
__device__ __forceinline__ void st_rlx2x32(void* p, uint32_t a, uint32_t b) { asm volatile("st.relaxed.gpu.global.v2.b32 [%0], {%1,%2};" :: "l"(p), "r"(a), "r"(b) : "memory"); }
__device__ __forceinline__ void st_rlx128(void* p, uint32_t a, uint32_t b, uint32_t c, uint32_t d) {
    asm volatile("st.relaxed.gpu.global.v4.b32 [%0], {%1,%2,%3,%4};" :: "l"(p), "r"(a), "r"(b), "r"(c), "r"(d) : "memory");
}
__device__ __forceinline__ void red_add(unsigned* p, uint32_t v) { asm volatile("red.relaxed.gpu.global.add.u32 [%0], %1;" :: "l"(p), "r"(v) : "memory"); }
__device__ __forceinline__ void st_rlx4x32(void* p, uint32_t a) { asm volatile("st.relaxed.gpu.global.v4.b32 [%0], {%1,%1,%1,%1};" :: "l"(p), "r"(a) : "memory"); }
__device__ __forceinline__ void st_rlx64(void* p, unsigned long long v) { asm volatile("st.relaxed.gpu.global.b64 [%0], %1;" :: "l"(p), "l"(v) : "memory"); }
__device__ __forceinline__ uint32_t tagf(float x, uint32_t tag) { return (__float_as_uint(x) & ~1u) | tag; }
__device__ __forceinline__ float untag(uint32_t w) { return __uint_as_float(w & ~1u); }

__device__ __forceinline__ uint32_t xor_or(uint32_t a, uint32_t b, uint32_t t) {
    uint32_t r; asm("lop3.b32 %0, %1, %2, %3, 0x7E;" : "=r"(r) : "r"(a), "r"(b), "r"(t)); return r;
}
__device__ __forceinline__ uint32_t or3(uint32_t a, uint32_t b, uint32_t c) {
    uint32_t r; asm("lop3.b32 %0, %1, %2, %3, 0xFE;" : "=r"(r) : "r"(a), "r"(b), "r"(c)); return r;
}
__device__ __forceinline__ uint32_t or_and1(uint32_t a, uint32_t b) {
    uint32_t r; asm("lop3.b32 %0, %1, %2, 1, 0xA8;" : "=r"(r) : "r"(a), "r"(b)); return r;
}
__device__ __forceinline__ void ld_rlx128_if(uint4& v, const void* p, uint32_t cond) {
    asm volatile("{\n.reg .pred p;\nsetp.ne.u32 p, %5, 0;\n@p ld.relaxed.gpu.global.v4.b32 {%0,%1,%2,%3}, [%4];\n}"
                 : "+r"(v.x), "+r"(v.y), "+r"(v.z), "+r"(v.w) : "l"(p), "r"(cond) : "memory");
}
__device__ __forceinline__ void ld_rlx2x64_if(uint4& v, const void* p, uint32_t cond) {
    asm volatile("{\n.reg .pred p;\n.reg .b64 a, b;\nsetp.ne.u32 p, %5, 0;\nmov.b64 a, {%0,%1};\nmov.b64 b, {%2,%3};\n"
                 "@p ld.relaxed.gpu.global.v2.b64 {a, b}, [%4];\nmov.b64 {%0,%1}, a;\nmov.b64 {%2,%3}, b;\n}"
                 : "+r"(v.x), "+r"(v.y), "+r"(v.z), "+r"(v.w) : "l"(p), "r"(cond) : "memory");
}
template <int N, bool W64, typename F>
__device__ __forceinline__ void gather128(uint4 (&v)[N], F addr, uint32_t tag) {
    auto stale = [&](const uint4& x) -> uint32_t {
        return W64 ? (xor_or(x.x, x.z, tag) & 1u) : or_and1(xor_or(x.x, x.y, tag), xor_or(x.z, x.w, tag));
    };
    auto any_stale = [&]() -> bool {
        uint32_t any = 0u;
#pragma unroll
        for (int i = 0; i < N; i++) any = W64 ? or3(any, xor_or(v[i].x, v[i].z, tag), 0u) : or3(any, xor_or(v[i].x, v[i].y, tag), xor_or(v[i].z, v[i].w, tag));
        return (any & 1u) != 0u;
    };
#pragma unroll
    for (int i = 0; i < N; i++) v[i] = W64 ? ld_rlx2x64(addr(i)) : ld_rlx128(addr(i));
    int it = 0;
#pragma unroll 1
    while (any_stale()) {
#pragma unroll
        for (int i = 0; i < N; i++) { if (W64) ld_rlx2x64_if(v[i], addr(i), stale(v[i])); else ld_rlx128_if(v[i], addr(i), stale(v[i])); }
        if (++it > SPIN_LIMIT) __trap();
    }
}
__device__ __forceinline__ void wait_any(const unsigned* p, uint32_t ntag) {
    int it = 0;
#pragma unroll 1
    while (true) {
        const uint32_t v = ld_rlx32(p);
        if ((v ^ ntag) & 1u) break;
        if (++it > SPIN_LIMIT) __trap();
    }
}
__global__ void __launch_bounds__(NTHREADS, 1)
fused_decode_kernel(Scratch* __restrict__ scr, const __nv_bfloat16* __restrict__ gx, const __nv_bfloat16* __restrict__ gc,
                    __nv_bfloat16* __restrict__ gout, const Hot hot, const __grid_constant__ Maps maps, const __grid_constant__ Sched tune) {
    extern __shared__ __align__(1024) unsigned char smem_raw[];
    const uint32_t sbase = smem_u32(smem_raw);
    unsigned char* sgen = smem_raw;
    const uint32_t misc = sbase + RING;
    auto bar = [&](int i) -> uint32_t { return misc + OFF_BAR + 8 * i; };

    const int tid = threadIdx.x, warp = tid >> 5, lane = tid & 31;
    const int cta = blockIdx.x;
    const bool att = cta < 128;
    const bool isW = !att || (cta & 3) == 3;
    const int wi = att ? (cta >> 2) : cta - 96;
    const int fi = 3 * (cta >> 2) + (cta & 3);
    const int modb = isW ? wi : 36 + fi;
    const bool has_mod = modb < 90;
    if (tid == 384) {
        mbar_init(bar(B_P1), 1);
        asm volatile("fence.mbarrier_init.release.cluster;" ::: "memory");
        mbar_expect_tx(bar(B_P1), 36864);
        const CUtensorMap* mp = &maps.wmod + (isW ? 0 : 1);
        const uint32_t dst = sbase + PRO_OFF + (isW ? 0 : 36864);
        const int c0 = 32 * (isW ? wi : cta);
#pragma unroll
        for (int j = 0; j < 3; j++) tma2d(dst + j * 12288, mp, c0, 192 * j, bar(B_P1));
    }
    const float LOG2E = 1.4426950408889634f;
    volatile int* ctl = reinterpret_cast<volatile int*>(sgen + RING + OFF_CTL);
    auto wait_count = [&](int idx, int thr) { int it = 0; while (ctl[idx] < thr) { if (++it > 16 * SPIN_LIMIT) __trap(); } };

    if (warp >= 12) {
        const uint32_t t0 = clk32();
        const int cls = att ? (isW ? 1 : 0) : 2;
        if (tid == 384) {
            mbar_init(bar(B_P2), 1);
            asm volatile("fence.mbarrier_init.release.cluster;" ::: "memory");
            if (isW ? att : has_mod) {
                mbar_expect_tx(bar(B_P2), 36864);
#pragma unroll 1
                for (int j = 0; j < 3; j++)
                    tma2d(sbase + PRO_OFF + (isW ? 36864 : 0) + j * 12288, &maps.wmod + (isW ? 1 : 0), 32 * (isW ? cta : modb), 192 * j, bar(B_P2));
            } else {
                mbar_arrive(bar(B_P2));
            }
        }
        if (warp != 12 && lane == 0) {
            if (warp == 15) { if (sbase & 1023u) __trap(); for (int i = 0; i < 7; i++) ctl[i] = 0; }
#pragma unroll 1
            for (int i = warp - 13; i < B_COUNT; i += 3)
                if (i != B_P1 && i != B_P2) mbar_init(bar(i), (i >= B_EMPTY && i < B_P1) ? 5 : ((i == B_PROFREE || i == B_ML) ? 8 : 1));
            asm volatile("fence.mbarrier_init.release.cluster;" ::: "memory");
        }
        asm volatile("bar.arrive 2, 384;" ::: "memory");
        asm volatile("bar.sync 10, 128;" ::: "memory");
        uint2* tab = reinterpret_cast<uint2*>(sgen + RING + OFF_TAB);
        if (warp == 15) {
            uint2 e[3];
#pragma unroll
            for (int r = 0; r < 3; r++) {
                const int m = min(32 * r + lane, MAXOPS - 1);
                asm volatile("ld.v2.u32 {%0,%1}, [%2];" : "=r"(e[r].x), "=r"(e[r].y) : "l"(&tune.ops[cls][m]));
            }
            const uint32_t ntag = ld_rlx32(&scr->epoch) & 1u;
            if (lane < 11) asm volatile("prefetch.tensormap [%0];" :: "l"(&maps.k + lane) : "memory");
#pragma unroll
            for (int r = 0; r < 3; r++) if (32 * r + lane < MAXOPS) tab[32 * r + lane] = e[r];
            asm volatile("bar.arrive 11, 64;" ::: "memory");
            asm volatile("bar.arrive 12, 64;" ::: "memory");
            if (!isW) {
                int it = 0;
                while (ctl[0] < hot.g_pw) { __nanosleep(500); if (++it > SPIN_LIMIT) __trap(); }
#pragma unroll 1
                for (int e2 = lane; e2 < 576; e2 += 32) st_rlx4x32(&scr->d[((e2 >> 4) * NF + fi) * 64 + (e2 & 15) * 4], ntag);
                asm volatile("bar.arrive 5, 416;" ::: "memory");
            }
            return;
        }
        if (warp == 14) {
            if (lane == 0) {
                const uint32_t ep = ld_rlx32(&scr->epoch);
                int it = 0;
#pragma unroll 1
                while (!(ctl[4] && ctl[5])) {
                    const uint4 c = ld_rlx128(scr->cnt[cta & (NREP - 1)]);
                    asm volatile("st.volatile.shared.v4.b32 [%0], {%1,%2,%3,%4};" :: "r"(misc + OFF_CTL),
                                 "r"(c.x - ep * TOTAL_KB), "r"(c.y - ep * (unsigned)NW), "r"(c.z - ep * (unsigned)NF), "r"(0) : "memory");
                    if (hot.poll_gap) { const uint32_t tw = clk32(); while ((int)(clk32() - tw) < hot.poll_gap) {} }
                    if (++it > SPIN_LIMIT) __trap();
                }
            }
            return;
        }
        const int nops = att ? NKV - NPRE + 9 : 9;
        if (warp == 13) {
            {
                uint32_t pend = att ? (1u << (2 + NPRE)) - 1u : 1u;
                const uint32_t wb = bar(lane < 2 ? B_P1 + lane : B_FULL + (lane - 2) % NPRE);
                int it = 0;
#pragma unroll 1
                while (pend) {
                    const uint32_t got = __ballot_sync(0xffffffffu, mbar_test(wb, 0)) & pend;
                    if (got) {
                        const uint32_t kb = 16u * __popc(got >> 2) + 36u * ((got & 1u) + (has_mod ? ((got >> 1) & 1u) : 0u));
                        if (lane < NREP) red_add(&scr->cnt[lane][0], kb);
                        if (lane >= 2 && ((got >> lane) & 1u)) { mbar_arrive(bar(B_EMPTY + lane - 2)); }
                        pend &= ~got;
                    }
                    if (++it > 16 * SPIN_LIMIT) __trap();
                }
            }
            asm volatile("bar.sync 11, 64;" ::: "memory");
#pragma unroll 1
            for (int m = 0; m < nops; m++) {
                const uint2 e = tab[m];
                const int op = (e.y >> 8) & 255;
                mbar_wait(bar((e.x >> 24) & 127u), e.x >> 31);
                __syncwarp();
                if (lane < NREP) red_add(&scr->cnt[lane][0], op < 72 ? 16u : 18u);
                if (lane == 0) { if (op < 64) { ctl[6] = op + 1; mbar_arrive(bar(B_EMPTY - B_FULL + ((e.x >> 24) & 127u))); } }
            }
            return;
        }
        auto kv_row = [&](int j) -> int {
            if (j < NSW) { const int f = j * 128 + cta, r = f / PER; return r * 4096 + (f - r * PER) * 64; }
            return (((cta >> 1) & 3) * 16 + (cta >> 3)) * 4096 + (2 * j + (cta & 1)) * 64;
        };
        const uint64_t pol = policy_stream();
        if (lane == 0 && att) {
#pragma unroll 1
            for (int i = 0; i < NPRE; i++) {
                int it = 0;
                while (ctl[0] < hot.g_kv0 + i * 2048 && (i >= hot.n_timed || (int)(clk32() - t0) < hot.t_kv0 + i * hot.dt_kv)) { if (++it > 16 * SPIN_LIMIT) __trap(); }
                mbar_expect_tx(bar(B_FULL + i), SLOT);
                tma3d(sbase + i * SLOT, &maps.k + (i & 1), 0, kv_row(i >> 1), 0, bar(B_FULL + i), pol);
            }
        }
        asm volatile("bar.sync 12, 64;" ::: "memory");
#pragma unroll 1
        for (int r = 0; r < 3; r++) {
            const uint2 e = tab[min(32 * r + lane, MAXOPS - 1)];
            const int op = (e.y >> 8) & 255;
            const uint32_t dst = sbase + (e.y & 255u) * 1024u;
            const uint32_t fb = bar((e.x >> 24) & 127u);
            const CUtensorMap* mp;
            int c0 = 0, c1, kind;
            if (op < 64) { mp = &maps.k + (op & 1); c1 = kv_row(op >> 1); kind = 0; }
            else if (op < 72) { mp = &maps.wo; c0 = 32 * (wi >> 1); c1 = 2048 * (wi & 1) + 256 * (op - 64); kind = 1; }
            else if (op < 78) { mp = &maps.g32 + (op & 1); c0 = 48 * fi + 16 * (fi & 1); c1 = 192 * ((op - 72) >> 1); kind = 2; }
            else if (op < 81) { mp = &maps.wd; c1 = 48 * fi + 16 * (op - 78); kind = 0; }
            else { mp = &maps.wm16; c0 = 5 * D_MODEL + 16 * wi; c1 = 0; kind = 3; }
            const int gmin = (int)(e.y >> 16) * 4;
            const int cnt = min(32, nops - 32 * r);
#pragma unroll 1
            for (int l = 0; l < cnt; l++) {
                if (lane == l) {
                    if ((e.x & 127u) != 127u) mbar_wait(bar(e.x & 127u), (e.x >> 7) & 1u);
                    if (((e.x >> 8) & 127u) != 127u) mbar_wait(bar((e.x >> 8) & 127u), (e.x >> 15) & 1u);
                    wait_count(0, gmin);
                    mbar_expect_tx(fb, op < 72 ? SLOT : FOP);
                    if (kind == 0) tma3d(dst, mp, 0, c1, 0, fb, pol);
                    else {
                        tma2dh(dst, mp, c0, c1, fb, pol);
                        if (kind == 2) tma2dh(dst + 12288, mp + 2, 48 * fi + 32 * (1 - (fi & 1)), c1, fb, pol);
                        if (kind == 3) { tma2dh(dst + 6144, mp, c0, 192, fb, pol); tma2dh(dst + 12288, mp, c0, 384, fb, pol); }
                    }
                }
                __syncwarp();
            }
        }
        if (lane == 0) { ctl[4] = 1; }
        return;
    }

    const uint32_t epoch = ld_rlx32(&scr->epoch);
    float* red = reinterpret_cast<float*>(sgen + RING + OFF_RED);

    if (warp >= 8) {
        const int b = warp - 8;
        const bool q4 = lane < 16;
        const int ql = 4 * lane, q4off = 512 + 4 * (lane & 15) - ql;
        auto qoff = [&](int i) -> int { return i < 4 ? 128 * i : q4off; };
        uint2 xw[5], cw[5];
#pragma unroll
        for (int i = 0; i < 5; i++) {
            xw[i] = *reinterpret_cast<const uint2*>(gx + b * D_MODEL + ql + qoff(i));
            cw[i] = *reinterpret_cast<const uint2*>(gc + b * D_MODEL + ql + qoff(i));
        }
        unsigned char* arow = sgen + RING + OFF_ACT + (b * APITCH + ql) * 2;
#pragma unroll
        for (int i = 0; i < 5; i++) {
            const float c0 = bf_lo(cw[i].x), c1 = bf_hi(cw[i].x), c2 = bf_lo(cw[i].y), c3 = bf_hi(cw[i].y);
            const uint2 sc2 = make_uint2(pack_bf2(__fdividef(c0, 1.0f + ex2(-LOG2E * c0)), __fdividef(c1, 1.0f + ex2(-LOG2E * c1))),
                                         pack_bf2(__fdividef(c2, 1.0f + ex2(-LOG2E * c2)), __fdividef(c3, 1.0f + ex2(-LOG2E * c3))));
            *reinterpret_cast<uint2*>(arow + qoff(i) * 2) = sc2;
            if (isW) *reinterpret_cast<uint2*>(arow + qoff(i) * 2 - (RING + OFF_ACT - SILU_OFF)) = sc2;
        }
        asm volatile("bar.arrive 3, 384;" ::: "memory");
        const uint32_t ntag = epoch & 1u;
        const int nph = att ? (isW ? 1 : 2) : 0;
        if (!att) asm volatile("bar.sync 6, 384;" ::: "memory");
#pragma unroll 1
        for (int ph = 0; ph < nph; ph++) {
            const unsigned* pm = &scr->mod[b * N_MOD + ph * 3 * D_MODEL + ql];
            uint2 shp[5], scp[5];
            {
                wait_any(&scr->mod[b * N_MOD + ph * 3 * D_MODEL + 8 * cta], ntag);
                uint4 mv[10];
                gather128<10, false>(mv, [&](int i) { return pm + qoff(i % 5) + (i / 5) * D_MODEL; }, ntag ^ 1u);
#pragma unroll
                for (int i = 0; i < 5; i++) {
                    shp[i] = make_uint2(__byte_perm(mv[i].x, mv[i].y, 0x7632), __byte_perm(mv[i].z, mv[i].w, 0x7632));
                    scp[i] = make_uint2(badd2(0x3f803f80u, __byte_perm(mv[i + 5].x, mv[i + 5].y, 0x7632)), badd2(0x3f803f80u, __byte_perm(mv[i + 5].z, mv[i + 5].w, 0x7632)));
                }
            }
            if (ph == 1) {
                uint2 gap[5];
                {
                    uint4 mv[5];
                    gather128<5, false>(mv, [&](int i) { return pm + qoff(i) - D_MODEL; }, ntag ^ 1u);
#pragma unroll
                    for (int i = 0; i < 5; i++) gap[i] = make_uint2(__byte_perm(mv[i].x, mv[i].y, 0x7632), __byte_perm(mv[i].z, mv[i].w, 0x7632));
                }
                asm volatile("bar.sync 7, 384;" ::: "memory");
                const unsigned* py = &scr->y[b * D_MODEL + ql];
                wait_count(1, hot.thr_y);
                uint4 yv[10];
                gather128<10, false>(yv, [&](int i) { return py + qoff(i % 5) + (i / 5) * 4 * D_MODEL; }, ntag ^ 1u);
                __syncwarp();
#pragma unroll
                for (int i = 0; i < 5; i++) {
                    const uint32_t y01 = pack_bf2(untag(yv[i].x) + untag(yv[i + 5].x), untag(yv[i].y) + untag(yv[i + 5].y));
                    const uint32_t y23 = pack_bf2(untag(yv[i].z) + untag(yv[i + 5].z), untag(yv[i].w) + untag(yv[i + 5].w));
                    xw[i] = make_uint2(badd2(xw[i].x, bmul2(gap[i].x, y01)), badd2(xw[i].y, bmul2(gap[i].y, y23)));
                }
            } else {
                asm volatile("bar.sync 6, 384;" ::: "memory");
            }
            const float x0 = bf_lo(__shfl_sync(0xffffffffu, xw[0].x, 0));
            float s1[5], s2[5];
#pragma unroll
            for (int i = 0; i < 5; i++) {
                const float d0 = bf_lo(xw[i].x) - x0, d1 = bf_hi(xw[i].x) - x0, d2 = bf_lo(xw[i].y) - x0, d3 = bf_hi(xw[i].y) - x0;
                s1[i] = (d0 + d1) + (d2 + d3);
                s2[i] = fmaf(d0, d0, d1 * d1) + fmaf(d2, d2, d3 * d3);
            }
            float sa = ((s1[0] + s1[1]) + (s1[2] + s1[3])) + (q4 ? s1[4] : 0.f);
            float sb = ((s2[0] + s2[1]) + (s2[2] + s2[3])) + (q4 ? s2[4] : 0.f);
#pragma unroll
            for (int o = 16; o > 0; o >>= 1) { sa += __shfl_xor_sync(0xffffffffu, sa, o); sb += __shfl_xor_sync(0xffffffffu, sb, o); }
            sa *= (1.0f / 576.0f);
            const float mean = x0 + sa;
            const float var = bfr(fmaxf(fmaf(-sa, sa, sb * (1.0f / 576.0f)), 0.f));
            const uint32_t mb2 = pack_bf2(mean, mean);
            float sq; asm("sqrt.approx.f32 %0, %1;" : "=f"(sq) : "f"(bfr(var + 1e-5f)));
            const float rden = __fdividef(1.0f, bfr(sq));
#pragma unroll
            for (int i = 0; i < 5; i++) {
                const uint32_t d01 = bsub2(xw[i].x, mb2), d23 = bsub2(xw[i].y, mb2);
                const uint32_t n01 = pack_bf2(bf_lo(d01) * rden, bf_hi(d01) * rden), n23 = pack_bf2(bf_lo(d23) * rden, bf_hi(d23) * rden);
                *reinterpret_cast<uint2*>(arow + qoff(i) * 2) = make_uint2(badd2(bmul2(n01, scp[i].x), shp[i].x), badd2(bmul2(n23, scp[i].y), shp[i].y));
            }
            asm volatile("bar.arrive %0, %1;" :: "r"(4 + ph), "r"(384 + 32 * ph) : "memory");
        }
        if (isW) {
            const int lk = (lane & 7) + 8 * (lane >> 4);
            const uint32_t a = sbase + 11 * SLOT + (144 * b + lk) * 32 + ((((lane >> 3) ^ (lk >> 2)) & 1) << 4);
            float acc[2][4] = {};
            asm volatile("bar.sync 9, 128;" ::: "memory");
            uint32_t sf[9][2];
            const uint32_t sa = sbase + SILU_OFF + (((lane >> 2) & 3) * APITCH + 2 * (lane & 3) + 144 * b) * 2;
#pragma unroll
            for (int s = 0; s < 9; s++) { sf[s][0] = lds32(sa + s * 32); sf[s][1] = lds32(sa + s * 32 + 16); }
            mbar_wait(bar(B_T + 8), 0);
#pragma unroll
            for (int s = 0; s < 9; s++) {
                uint32_t w[4];
                ldsm4t(w, a + s * 512);
                mma16816(acc[s & 1], w, sf[s][0], sf[s][1]);
            }
            *reinterpret_cast<float2*>(red + 2304 + b * 64 + ((lane >> 2) + 8 * ((lane >> 1) & 1)) * 4 + 2 * (lane & 1)) =
                (lane & 2) ? make_float2(acc[0][2] + acc[1][2], acc[0][3] + acc[1][3]) : make_float2(acc[0][0] + acc[1][0], acc[0][1] + acc[1][1]);
            asm volatile("bar.arrive 14, 384;" ::: "memory");
            return;
        }
        if (tid == 256) { ctl[5] = 1; }
        asm volatile("bar.sync 8, 384;" ::: "memory");
        float gs[2], us[2];
#pragma unroll
        for (int r = 0; r < 2; r++) {
            const float* rp = red + (r ? 4 + (b & 1) : b) * 64 + lane;
            gs[r] = ((rp[0] + rp[384]) + (rp[2 * 384] + rp[3 * 384])) + ((rp[4 * 384] + rp[5 * 384]) + (rp[6 * 384] + rp[7 * 384]));
            rp += 32;
            us[r] = ((rp[0] + rp[384]) + (rp[2 * 384] + rp[3 * 384])) + ((rp[4 * 384] + rp[5 * 384]) + (rp[6 * 384] + rp[7 * 384]));
        }
        asm volatile("bar.arrive 15, 384;" ::: "memory");
#pragma unroll
        for (int r = 0; r < 2; r++) {
            const float gv = bfr(gs[r]), uv = bfr(us[r]);
            const float u2 = (-2.0f * 0.7978845608028654f * LOG2E) * (gv + 0.044715f * gv * gv * gv);
            const float ge = bfr(__fdividef(gv, 1.0f + ex2(u2)));
            const int col = 8 * (4 * r + b) + ((fi & 1) ? (r ? -32 : 16) : 0) + (lane >> 2);
            if (r == 0 || b < 2) reinterpret_cast<__nv_bfloat16*>(sgen + RING + OFF_Q)[(lane & 3) * 56 + col] = __float2bfloat16_rn(ge * uv);
        }
        asm volatile("bar.arrive 13, 384;" ::: "memory");
        return;
    }

    uint32_t slots;
    asm volatile("ld.u16 %0, [%1];" : "=r"(slots) : "l"(&tune.slot[isW ? 1 : 0][2 * lane]));
    const int g = lane >> 2, t = lane & 3;
    const int ks0 = warp < 4 ? 5 * warp : 20 + 4 * (warp - 4);
    const int nks = warp < 4 ? 5 : 4;
    const int lk = (lane & 7) + 8 * (lane >> 4);
    const int mh = (lane >> 3) & 1;
    const uint32_t bfrag = misc + OFF_ACT + ((g & 3) * APITCH + 2 * t) * 2;
    asm volatile("bar.sync 2, 384;" ::: "memory");
    const uint32_t ntag = epoch & 1u, tag = ntag ^ 1u;
    unsigned long long* opub = &scr->o[(cta >> 3) * 512 + warp * 64 + (cta & 7) * 8 + g];
    unsigned* ypub = &scr->y[((wi & 1) * 4 + warp) * D_MODEL + 32 * (wi >> 1) + lane];
    if (tid < 128) {
        if (att) st_rlx32(&scr->q[warp * HQD + 32 * cta + (lane & 16) + 4 * ((lane & 7) >> 1) + (lane & 1) + 2 * ((lane >> 3) & 1)], ntag);
        if (has_mod) st_rlx32(&scr->mod[warp * N_MOD + 32 * modb + lane], ntag);
        if (isW) st_rlx32(ypub, ntag);
    }
    if (att) {
        if (t == 0) st_rlx64(opub, ntag);
        if (tid < 4) st_rlx64(&scr->ml[cta * 4 + tid], ntag);
    }

#pragma unroll 1
    for (int ph = 0; ph < (att ? 2 : 1); ph++) {
        const bool active = ph == 1 || has_mod;
        uint32_t pa[5][2][4];
        if (active) {
            mbar_wait(bar(B_P1 + (ph ^ (isW ? 0 : 1))), 0);
            const uint32_t rowa = sbase + PRO_OFF + ph * 36864 + (ks0 * 16 + lk) * 64;
#pragma unroll
            for (int s = 0; s < 5; s++)
#pragma unroll
                for (int j = 0; j < 2; j++)
                    if (s < nks) ldsm4t(pa[s][j], rowa + s * 1024 + (((2 * j + mh) ^ ((lk >> 1) & 3)) << 4));
        }
        if (ph == 1) { __syncwarp(); if (lane == 0) mbar_arrive(bar(B_PROFREE)); }
        asm volatile("bar.sync %0, 384;" :: "r"(3 + ph) : "memory");
        if (active) {
            float acc[2][4] = {};
#pragma unroll
            for (int s = 0; s < 5; s++) if (s < nks) {
                const uint32_t b0 = lds32(bfrag + (ks0 + s) * 32), b1 = lds32(bfrag + (ks0 + s) * 32 + 16);
                mma16816(acc[0], pa[s][0], b0, b1);
                mma16816(acc[1], pa[s][1], b0, b1);
            }
            float* rw = red + warp * 128 + (g + 8 * (t >> 1)) * 4 + 2 * (t & 1);
#pragma unroll
            for (int j = 0; j < 2; j++)
                *reinterpret_cast<float2*>(rw + 64 * j) = (t & 2) ? make_float2(acc[j][2], acc[j][3]) : make_float2(acc[j][0], acc[j][1]);
        }
        if (ph == 0) asm volatile("bar.arrive 6, 384;" ::: "memory");
        cbar();
        if (active && tid < 128) {
            float s = 0.f;
#pragma unroll
            for (int w = 0; w < 8; w++) s += red[w * 128 + lane * 4 + warp];
            unsigned* dst = ph == 0 ? &scr->mod[warp * N_MOD + 32 * modb + lane]
                                    : &scr->q[warp * HQD + 32 * cta + (lane & 16) + 4 * ((lane & 7) >> 1) + (lane & 1) + 2 * ((lane >> 3) & 1)];
            st_rlx32(dst, (pack_bf2(0.f, s) & 0xffff0000u) | tag);
        }
    }

    if (att) {
        const float SCALE = 0.08838834764831845f;
        const int own_reg = ((cta >> 1) & 3) * 16 + (cta >> 3);
        uint32_t qf[8][2];
        float o[8][4], ex[8];
        float m0, m1, l0, l1, fin, me0, me1, le0, le1;
        const int kch = lane >> 4;
        int j = warp, qd = 0;
#pragma unroll 1
        while (j < 32) {
            const bool sweep = j < NSW;
            if (sweep ? qd == 0 : j < NSW + 2) {
                const int reg = sweep ? (j * 128 + cta) / PER : own_reg;
                const unsigned* pq = &scr->q[(reg >> 4) * HQD + (reg & 15) * 256 + (g & 1) * 128 + 4 * t];
                uint4 qv[8];
                gather128<8, false>(qv, [&](int i) { return pq + 16 * i; }, tag);
                __syncwarp();
#pragma unroll
                for (int ks = 0; ks < 8; ks++) { qf[ks][0] = __byte_perm(qv[ks].x, qv[ks].y, 0x7632); qf[ks][1] = __byte_perm(qv[ks].z, qv[ks].w, 0x7632); }
#pragma unroll
                for (int jj = 0; jj < 8; jj++) { o[jj][0] = o[jj][1] = o[jj][2] = o[jj][3] = 0.f; }
                m0 = m1 = -INFINITY; l0 = l1 = 0.f;
            }
            if (j >= 30) {
                const int f0 = own_reg * PER + (cta & 1) * NSW;
                uint4 pv[8];
                gather128<8, false>(pv, [&](int i) { const int f = f0 + min(warp + 8 * (i & 3), NSW - 1);
                                                     return i < 4 ? &scr->part[f * 32 + lane] : &scr->pml[f * 2]; }, tag);
                __syncwarp();
                me0 = fmaxf(fmaxf(bf_hi(pv[4].y), bf_hi(pv[5].y)), fmaxf(bf_hi(pv[6].y), bf_hi(pv[7].y)));
                me1 = fmaxf(fmaxf(bf_hi(pv[4].w), bf_hi(pv[5].w)), fmaxf(bf_hi(pv[6].w), bf_hi(pv[7].w)));
#pragma unroll
                for (int dt = 0; dt < 8; dt++) ex[dt] = 0.f;
                le0 = le1 = 0.f;
#pragma unroll
                for (int i = 0; i < 4; i++) {
                    const bool ok = warp + 8 * i < NSW;
                    const float w0 = ok ? ex2((bf_hi(pv[4 + i].y) - me0) * LOG2E) : 0.f, w1 = ok ? ex2((bf_hi(pv[4 + i].w) - me1) * LOG2E) : 0.f;
                    le0 = fmaf(w0, untag(pv[4 + i].x), le0); le1 = fmaf(w1, untag(pv[4 + i].z), le1);
                    const float sc = __uint_as_float((((t & 1) ? pv[4 + i].w : pv[4 + i].y) & 0xfffeu) << 15);
                    const float w = ((t & 1) ? w1 : w0) * sc * (1.0f / 32766.0f);
                    const uint32_t u[4] = {pv[i].x, pv[i].y, pv[i].z, pv[i].w};
#pragma unroll
                    for (int e = 0; e < 4; e++) {
                        ex[2 * e] = fmaf(w, (float)(((int)(u[e] << 16) >> 16) & ~1), ex[2 * e]);
                        ex[2 * e + 1] = fmaf(w, (float)((int)u[e] >> 16), ex[2 * e + 1]);
                    }
                }
            }
            const int wr = (sweep ? qd : (warp & 3)) * 16;
            const int krow = wr + (lane & 7) + 8 * ((lane >> 3) & 1);
            const int vrow = wr + lk;
            const uint32_t ikv = __shfl_sync(0xffffffffu, slots, j);
            const uint32_t sk = ikv & 15u, uk = ikv >> 4, sv = (ikv >> 8) & 15u, uv = ikv >> 12;
            {
                int it = 0;
                if (j >= 6) while (ctl[6] <= 2 * j - 5) { __nanosleep(64); if (++it > SPIN_LIMIT) __trap(); }
            }
            mbar_wait(bar(B_FULL + sk), uk & 1);
            const uint32_t kb = sbase + sk * SLOT + krow * 128;
            float sa[4] = {0.f, 0.f, 0.f, 0.f}, sb[4] = {0.f, 0.f, 0.f, 0.f};
#pragma unroll
            for (int ks = 0; ks < 4; ks++) {
                uint32_t a[4], a2[4];
                ldsm4(a, kb + (((2 * ks + kch) ^ (krow & 7)) << 4));
                ldsm4(a2, kb + 8192 + (((2 * ks + kch) ^ (krow & 7)) << 4));
                mma16816(sa, a, qf[ks][0], qf[ks][1]);
                mma16816(sb, a2, qf[ks + 4][0], qf[ks + 4][1]);
            }
            __syncwarp();
            if (lane == 0) mbar_arrive(bar(B_EMPTY + sk));
            float s[4];
            {
                const uint32_t r01 = pack_bf2(sa[0] + sb[0], sa[1] + sb[1]), r23 = pack_bf2(sa[2] + sb[2], sa[3] + sb[3]);
                const uint32_t u01 = pack_bf2(bf_lo(r01) * SCALE, bf_hi(r01) * SCALE), u23 = pack_bf2(bf_lo(r23) * SCALE, bf_hi(r23) * SCALE);
                s[0] = bf_lo(u01); s[1] = bf_hi(u01); s[2] = bf_lo(u23); s[3] = bf_hi(u23);
            }
            float x0 = fmaxf(s[0], s[2]), x1 = fmaxf(s[1], s[3]);
#pragma unroll
            for (int of = 4; of < 32; of <<= 1) {
                x0 = fmaxf(x0, __shfl_xor_sync(0xffffffffu, x0, of));
                x1 = fmaxf(x1, __shfl_xor_sync(0xffffffffu, x1, of));
            }
            if (x0 > m0 || x1 > m1) {
                const float n0 = fmaxf(m0, x0), n1 = fmaxf(m1, x1);
                const float f0 = ex2((m0 - n0) * LOG2E), f1 = ex2((m1 - n1) * LOG2E);
                m0 = n0; m1 = n1; l0 *= f0; l1 *= f1;
#pragma unroll
                for (int jj = 0; jj < 8; jj++) { o[jj][0] *= f0; o[jj][1] *= f1; o[jj][2] *= f0; o[jj][3] *= f1; }
            }
            const float p0 = ex2((s[0] - m0) * LOG2E), p1 = ex2((s[1] - m1) * LOG2E);
            const float p2 = ex2((s[2] - m0) * LOG2E), p3 = ex2((s[3] - m1) * LOG2E);
            l0 += p0 + p2; l1 += p1 + p3;
            const uint32_t pb0 = movtrans(pack_bf2(p0, p1)), pb1 = movtrans(pack_bf2(p2, p3));
            if (j >= 30) {
#pragma unroll
                for (int of = 4; of < 32; of <<= 1) {
                    l0 += __shfl_xor_sync(0xffffffffu, l0, of);
                    l1 += __shfl_xor_sync(0xffffffffu, l1, of);
                }
                float4* mls = reinterpret_cast<float4*>(sgen + RING + OFF_ML);
                {
                    const float n0 = fmaxf(m0, me0), n1 = fmaxf(m1, me1);
                    l0 = l0 * ex2((m0 - n0) * LOG2E) + le0 * ex2((me0 - n0) * LOG2E);
                    l1 = l1 * ex2((m1 - n1) * LOG2E) + le1 * ex2((me1 - n1) * LOG2E);
                    if (lane == 0) { mls[warp] = make_float4(n0, n1, l0, l1); mbar_arrive(bar(B_ML)); }
                }
                mbar_wait(bar(B_ML), 0);
                const float4 mw = mls[lane & 7];
                float M0 = mw.x, M1 = mw.y;
#pragma unroll
                for (int of = 1; of < 8; of <<= 1) {
                    M0 = fmaxf(M0, __shfl_xor_sync(0xffffffffu, M0, of));
                    M1 = fmaxf(M1, __shfl_xor_sync(0xffffffffu, M1, of));
                }
                float L0 = mw.z * ex2((mw.x - M0) * LOG2E), L1 = mw.w * ex2((mw.y - M1) * LOG2E);
#pragma unroll
                for (int of = 1; of < 8; of <<= 1) {
                    L0 += __shfl_xor_sync(0xffffffffu, L0, of);
                    L1 += __shfl_xor_sync(0xffffffffu, L1, of);
                }
                if (tid < 4) st_rlx64(&scr->ml[cta * 4 + tid], (unsigned long long)tagf((tid & 1) ? L1 : L0, tag) | ((unsigned long long)__float_as_uint((tid & 1) ? M1 : M0) << 32));
                const float Mh = (t & 1) ? M1 : M0, rl = __fdividef(1.0f, (t & 1) ? L1 : L0);
                fin = ex2((((t & 1) ? m1 : m0) - Mh) * LOG2E) * rl;
                const float fe = ex2((((t & 1) ? me1 : me0) - Mh) * LOG2E) * rl;
#pragma unroll
                for (int dt = 0; dt < 8; dt++) ex[dt] *= fe;
            }
            mbar_wait(bar(B_FULL + sv), uv & 1);
            const uint32_t vb = sbase + sv * SLOT + vrow * 128;
#pragma unroll
            for (int dt = 0; dt < 8; dt++) {
                uint32_t a[4];
                ldsm4t(a, vb + (dt >> 2) * 8192 + (((2 * (dt & 3) + mh) ^ (vrow & 7)) << 4));
                mma16816(o[dt], a, pb0, pb1);
            }
            __syncwarp();
            if (lane == 0) mbar_arrive(bar(B_EMPTY + sv));
            if (!sweep) { j += 2; continue; }
            if (++qd < 4) continue;
            {
#pragma unroll
                for (int of = 4; of < 32; of <<= 1) {
                    l0 += __shfl_xor_sync(0xffffffffu, l0, of);
                    l1 += __shfl_xor_sync(0xffffffffu, l1, of);
                }
                float v[8], mx = 1e-30f;
#pragma unroll
                for (int dt = 0; dt < 8; dt++) {
                    const float lo = (t & 1) ? o[dt][1] : o[dt][0], hi = (t & 1) ? o[dt][3] : o[dt][2];
                    v[dt] = (t & 2) ? hi : lo;
                    mx = fmaxf(mx, fabsf(v[dt]));
                }
#pragma unroll
                for (int of = 2; of < 32; of <<= 1) mx = fmaxf(mx, __shfl_xor_sync(0xffffffffu, mx, of));
                const uint32_t sb = (__float_as_uint(mx) + 0xffffu) >> 16;
                const float q = __fdividef(32766.0f, __uint_as_float(sb << 16));
                uint32_t u[4];
#pragma unroll
                for (int e = 0; e < 4; e++)
                    u[e] = ((uint32_t)(2 * __float2int_rn(0.5f * q * v[2 * e])) & 0xfffeu) | ((uint32_t)__float2int_rn(q * v[2 * e + 1]) << 16) | tag;
                const uint32_t so = __shfl_xor_sync(0xffffffffu, sb, 1);
                const int f = j * 128 + cta;
                st_rlx128(&scr->part[f * 32 + lane], u[0], u[1], u[2], u[3]);
                if (lane == 0 || lane == 4)
                    st_rlx128(&scr->pml[f * 2 + (lane >> 2)], tagf(l0, tag), __float_as_uint(m0) | (sb << 1) | tag, tagf(l1, tag), __float_as_uint(m1) | (so << 1) | tag);
            }
            qd = 0;
            j += 8;
            if (j >= NSW) j = NSW + ((NSW ^ (warp >> 2)) & 1);
        }
        float* rw = red + warp * 288 + 144 * (t & 1) + g + 8 * (t >> 1);
#pragma unroll
        for (int dt = 0; dt < 8; dt++) {
            const float lo = (t & 1) ? o[dt][1] : o[dt][0], hi = (t & 1) ? o[dt][3] : o[dt][2];
            rw[16 * dt] = fmaf(fin, (t & 2) ? hi : lo, ex[dt]);
        }
        cbar();
        const int k = (2 * warp + (g & 1)) * 16 + 2 * (g >> 1) + (t & 1) + 8 * (t >> 1);
        const float* rp = red + k + 16 * (warp >> 2);
        const float val = ((rp[0] + rp[288]) + (rp[2 * 288] + rp[3 * 288])) + ((rp[4 * 288] + rp[5 * 288]) + (rp[6 * 288] + rp[7 * 288]));
        const uint32_t u = __float_as_uint(val);
        const uint32_t hb = t == 0 ? ((((u + 0xffffu + ((u >> 17) & 1u)) >> 16) & 0xfffeu) | tag) : (pack_bf2(val, 0.f) & 0xffffu);
        const uint32_t pr = hb | (__shfl_down_sync(0xffffffffu, hb, 1) << 16);
        const uint32_t p2 = __shfl_down_sync(0xffffffffu, pr, 2);
        if (t == 0) st_rlx64(opub, (unsigned long long)pr | ((unsigned long long)p2 << 32));
    }

    if (isW) {
        const int kvh = 8 * (wi & 1) + warp;
        const unsigned long long* po = &scr->o[kvh * 512 + lane * 2];
        const unsigned long long* pm = &scr->ml[(kvh * 8 + 2 * t) * 4];
        const uint32_t wslot = att ? (hot.wo_slots >> (4 * warp)) & 15u : warp;
        const uint32_t wb = sbase + wslot * SLOT + lk * 64;
        const uint32_t wx = (lk >> 1) & 3;
        mbar_wait(bar(B_T + warp), 0);
        constexpr int NPF = 7;
        uint32_t wa[NPF][2][4];
#pragma unroll
        for (int i = 0; i < NPF; i++) { ldsm4t(wa[i][0], wb + i * 1024 + ((mh ^ wx) << 4)); ldsm4t(wa[i][1], wb + i * 1024 + (((2 + mh) ^ wx) << 4)); }
        if (!att) {
            int it = 0;
            while (ctl[0] < hot.g_x) { __nanosleep(200); if (++it > SPIN_LIMIT) __trap(); }
            const unsigned long long* pw = &scr->ml[(kvh * 8 + g) * 4];
            it = 0;
#pragma unroll 1
            while (__any_sync(0xffffffffu, ((ld_rlx32(pw) ^ tag) & 1u) != 0u)) { if (++it > SPIN_LIMIT) __trap(); }
        }
        uint4 ob[10];
        gather128<10, true>(ob, [&](int i) { return i < 8 ? po + 64 * i : pm + (i - 8) * 4; }, tag);
        __syncwarp();
        float acc[2][2][4] = {};
#pragma unroll
        for (int ks = 0; ks < 16; ks++) {
            const uint32_t b0 = ((ks & 1) ? ob[ks >> 1].z : ob[ks >> 1].x) & ~1u, b1 = (ks & 1) ? ob[ks >> 1].w : ob[ks >> 1].y;
            mma16816(acc[ks >> 3][0], wa[ks % NPF][0], b0, b1);
            mma16816(acc[ks >> 3][1], wa[ks % NPF][1], b0, b1);
            if (ks + NPF < 16) {
                ldsm4t(wa[ks % NPF][0], wb + (ks + NPF) * 1024 + ((mh ^ wx) << 4));
                ldsm4t(wa[ks % NPF][1], wb + (ks + NPF) * 1024 + (((2 + mh) ^ wx) << 4));
            }
        }
        float yv[4] = {0.f, 0.f, 0.f, 0.f};
#pragma unroll
        for (int hd = 0; hd < 2; hd++) {
            const float la = untag(hd ? ob[8].z : ob[8].x), ma = __uint_as_float(hd ? ob[8].w : ob[8].y);
            const float lb = untag(hd ? ob[9].z : ob[9].x), mb = __uint_as_float(hd ? ob[9].w : ob[9].y);
            const float M = fmaxf(ma, mb);
            float fa = la * ex2((ma - M) * LOG2E), fb = lb * ex2((mb - M) * LOG2E);
            const float inv = __fdividef(1.0f, fa + fb);
            fa *= inv; fb *= inv;
#pragma unroll
            for (int c = 0; c < 2; c++) {
                yv[2 * c] += fa * acc[hd][c][0] + fb * acc[hd][c][1];
                yv[2 * c + 1] += fa * acc[hd][c][2] + fb * acc[hd][c][3];
            }
        }
        float* r2 = reinterpret_cast<float*>(sgen + RING + OFF_ACT);
#pragma unroll
        for (int c = 0; c < 4; c++) r2[warp * 128 + t * 32 + ((8 * (c + t) + g) & 31)] = yv[c];
        cbar();
        if (tid < 128) {
            const float* rp = r2 + warp * 32 + ((lane + 8 * warp) & 31);
            const float s = ((rp[0] + rp[128]) + (rp[256] + rp[384])) + ((rp[512] + rp[640]) + (rp[768] + rp[896]));
            st_rlx32(ypub, tagf(s, tag));
            if (tid < NREP) red_add(&scr->cnt[lane][1], 1u);
        }
        float x1 = 0.f;
        const int oc = 16 * wi + (tid & 15), ob_ = (tid >> 4) & 3, oi = (tid & 15) * 4 + ob_;
        if (tid < 64) {
            uint32_t v[3];
            int it = 0;
#pragma unroll 1
            do {
                v[0] = ld_rlx32(&scr->y[ob_ * D_MODEL + oc]); v[1] = ld_rlx32(&scr->y[(4 + ob_) * D_MODEL + oc]);
                v[2] = ld_rlx32(&scr->mod[ob_ * N_MOD + 2 * D_MODEL + oc]);
                if (++it > SPIN_LIMIT) __trap();
            } while (or_and1(xor_or(v[0], v[1], tag), v[2] ^ tag));
            x1 = bfr(__bfloat162float(gx[ob_ * D_MODEL + oc]) + bfr(bf_hi(v[2]) * bfr(untag(v[0]) + untag(v[1]))));
        }
        wait_count(2, hot.thr_d);
        if (tid == 0) ctl[5] = 1;
        const unsigned* pd = &scr->d[wi * NF * 64 + tid * 4];
        uint4 v[6];
        gather128<6, false>(v, [&](int i) { return pd + i * 1024; }, tag);
        __syncwarp();
        float s0 = 0.f, s1 = 0.f, s2 = 0.f, s3 = 0.f;
#pragma unroll
        for (int i = 0; i < 6; i++) {
            s0 += untag(v[i].x); s1 += untag(v[i].y); s2 += untag(v[i].z); s3 += untag(v[i].w);
        }
        s0 += __shfl_xor_sync(0xffffffffu, s0, 16); s1 += __shfl_xor_sync(0xffffffffu, s1, 16);
        s2 += __shfl_xor_sync(0xffffffffu, s2, 16); s3 += __shfl_xor_sync(0xffffffffu, s3, 16);
        float* fin = red + 1024;
        if (lane < 16) *reinterpret_cast<float4*>(fin + warp * 64 + lane * 4) = make_float4(s0, s1, s2, s3);
        asm volatile("bar.sync 14, 384;" ::: "memory");
        if (tid < 64) {
            const float* gp = red + 2304 + oi;
            const float gb = bfr((gp[0] + gp[64]) + (gp[128] + gp[192]));
            const float* rp = fin + oi;
            const float s = ((rp[0] + rp[64]) + (rp[128] + rp[192])) + ((rp[256] + rp[320]) + (rp[384] + rp[448]));
            gout[ob_ * D_MODEL + oc] = __float2bfloat16_rn(x1 + bfr(gb * bfr(s)));
            if (wi == 0 && tid == 0) scr->epoch = epoch + 1u;
        }
        return;
    }

    asm volatile("bar.arrive 7, 384;" ::: "memory");
    {
        uint32_t ga[5][5][4];
        uint32_t last[5];
#pragma unroll 1
        for (int i = 2 * (ks0 / 12); i < 2 * ((ks0 + nks - 1) / 12) + 2; i++) mbar_wait(bar(B_T + i), 0);
#pragma unroll
        for (int s = 0; s < 5; s++) if (s < nks) {
            const int ks = ks0 + s, bx = ks / 12, r = (ks - 12 * bx) * 16 + lk;
            const uint32_t ra = sbase + (2 * bx + mh) * FOP;
#pragma unroll
            for (int j = 0; j < 4; j++) ldsm4t(ga[s][j], ra + r * 64 + ((j ^ ((lk >> 1) & 3)) << 4));
            const uint32_t rb = ra + 12288 + r * 32;
            ldsm4t(ga[s][4], rb + (((lk >> 2) & 1) << 4));
            last[s] = rb + ((1 ^ ((lk >> 2) & 1)) << 4);
        }
        asm volatile("bar.sync 5, 416;" ::: "memory");
        float acc[6][4] = {};
        uint32_t hb[5][2], a5[2][4];
        hb[0][0] = lds32(bfrag + ks0 * 32); hb[0][1] = lds32(bfrag + ks0 * 32 + 16);
        hb[1][0] = lds32(bfrag + ks0 * 32 + 32); hb[1][1] = lds32(bfrag + ks0 * 32 + 48);
#pragma unroll
        for (int s = 0; s < 5; s++) if (s < nks) {
#pragma unroll
            for (int j = 0; j < 5; j++) mma16816(acc[j], ga[s][j], hb[s][0], hb[s][1]);
            if (s + 2 < 5) { hb[s + 2][0] = lds32(bfrag + (ks0 + s + 2) * 32); hb[s + 2][1] = lds32(bfrag + (ks0 + s + 2) * 32 + 16); }
            ldsm4t(a5[s & 1], last[s]);
            if (s > 0) mma16816(acc[5], a5[(s - 1) & 1], hb[s - 1][0], hb[s - 1][1]);
        }
        if (nks == 5) mma16816(acc[5], a5[0], hb[4][0], hb[4][1]); else mma16816(acc[5], a5[1], hb[3][0], hb[3][1]);
        float* rw = red + warp * 384 + (g + 8 * (t >> 1)) * 4 + 2 * (t & 1);
#pragma unroll
        for (int j = 0; j < 6; j++)
            *reinterpret_cast<float2*>(rw + 64 * j) = (t & 2) ? make_float2(acc[j][2], acc[j][3]) : make_float2(acc[j][0], acc[j][1]);
        asm volatile("bar.arrive 8, 384;" ::: "memory");
    }
    {
        const int cc = 2 * warp + mh;
        const uint32_t db = sbase + 6 * FOP + (cc >> 3) * 2048 + lk * 128 + (((cc & 7) ^ (lk & 7)) << 4);
        unsigned* dst = &scr->d[(warp * NF + fi) * 64 + (g + 8 * (t >> 1)) * 4 + 2 * (t & 1)];
        uint32_t a[3][5][4];
        float acc[5][4] = {};
        asm volatile("bar.sync 15, 384;" ::: "memory");
#pragma unroll
        for (int s = 0; s < 2; s++) {
            mbar_wait(bar(B_T + 6 + s), 0);
#pragma unroll
            for (int jj = 0; jj < 5; jj++) if (jj < 4 || warp < 4) ldsm4t(a[s][jj], db + s * FOP + jj * 4096);
        }
        if (tid < NREP) red_add(&scr->cnt[lane][2], 1u);
        asm volatile("bar.sync 13, 384;" ::: "memory");
        const uint32_t af = misc + OFF_Q + ((g & 3) * 56 + 2 * t) * 2;
        uint32_t bb[3][2];
#pragma unroll
        for (int s = 0; s < 3; s++) { bb[s][0] = lds32(af + s * 32); bb[s][1] = lds32(af + s * 32 + 16); }
#pragma unroll
        for (int s = 0; s < 2; s++)
#pragma unroll
            for (int jj = 0; jj < 5; jj++) if (jj < 4 || warp < 4) mma16816(acc[jj], a[s][jj], bb[s][0], bb[s][1]);
        mbar_wait(bar(B_T + 8), 0);
#pragma unroll
        for (int jj = 0; jj < 5; jj++) if (jj < 4 || warp < 4) ldsm4t(a[2][jj], db + 2 * FOP + jj * 4096);
#pragma unroll
        for (int jj = 0; jj < 5; jj++) if (jj < 4 || warp < 4) mma16816(acc[jj], a[2][jj], bb[2][0], bb[2][1]);
#pragma unroll
        for (int jj = 0; jj < 5; jj++) if (jj < 4 || warp < 4)
            st_rlx2x32(dst + jj * 8 * NF * 64, tagf((t & 2) ? acc[jj][2] : acc[jj][0], tag), tagf((t & 2) ? acc[jj][3] : acc[jj][1], tag));
    }
}

typedef CUresult (*EncodeFn)(CUtensorMap*, CUtensorMapDataType, cuuint32_t, void*, const cuuint64_t*, const cuuint64_t*,
                             const cuuint32_t*, const cuuint32_t*, CUtensorMapInterleave, CUtensorMapSwizzle,
                             CUtensorMapL2promotion, CUtensorMapFloatOOBfill);

void make2d(EncodeFn enc, CUtensorMap* m, const void* base, int rows, int cols, int boxc, int boxr, CUtensorMapSwizzle sw, int prom) {
    cuuint64_t dims[2] = {(cuuint64_t)cols, (cuuint64_t)rows};
    cuuint64_t str[1] = {(cuuint64_t)cols * 2};
    cuuint32_t box[2] = {(cuuint32_t)boxc, (cuuint32_t)boxr};
    cuuint32_t es[2] = {1, 1};
    enc(m, CU_TENSOR_MAP_DATA_TYPE_BFLOAT16, 2, const_cast<void*>(base), dims, str, box, es, CU_TENSOR_MAP_INTERLEAVE_NONE, sw,
        (CUtensorMapL2promotion)prom, CU_TENSOR_MAP_FLOAT_OOB_FILL_NONE);
}
void make3d(EncodeFn enc, CUtensorMap* m, const void* base, int rows, int chunks, int boxr, int prom) {
    cuuint64_t dims[3] = {64, (cuuint64_t)rows, (cuuint64_t)chunks};
    cuuint64_t str[2] = {(cuuint64_t)chunks * 128, 128};
    cuuint32_t box[3] = {64, (cuuint32_t)boxr, (cuuint32_t)chunks};
    cuuint32_t es[3] = {1, 1, 1};
    enc(m, CU_TENSOR_MAP_DATA_TYPE_BFLOAT16, 3, const_cast<void*>(base), dims, str, box, es, CU_TENSOR_MAP_INTERLEAVE_NONE,
        CU_TENSOR_MAP_SWIZZLE_128B, (CUtensorMapL2promotion)prom, CU_TENSOR_MAP_FLOAT_OOB_FILL_NONE);
}

struct Tune {
    float lead_start, lead_main, lead_tail, lead_late, lead_last;
    int n_start;
    int sw_tail;
    int wo_first, wo_step, wo_early;
    int n_timed, t_kv0, dt_kv;
    int poll_gap, thr_y, thr_d;
};
Tune g_tune = {3.25f, 3.4f, 3.25f, 2.85f, 2.35f, 13, 54, 54, 2, 4, 6, 1900, 670, 200, 8, 70};

void build_sched(const Tune& t, Sched& sc, Hot& hot) {
    int order[NKV];
    for (int p = 0; p < NKV; p++) order[p] = p;
    order[61] = 62; order[62] = 61;
    struct Item { int op, dst, wa, wb, full; double tau, bytes; bool late; };
    Item items[3][MAXOPS + NPRE];
    int cnt[3] = {0, 0, 0};
    hot.wo_slots = 0;
    for (int c = 0; c < 2; c++) {
        int uses[NSLOT] = {0};
        auto empty_code = [&](int s) { return (B_EMPTY + s) | (((uses[s] - 1) & 1) << 7); };
        auto put_kv = [&](int p, int s) {
            Item it{order[p], s * 16, 127, 127, (B_FULL + s) | ((uses[s] & 1) << 7), (double)p, (double)SLOT, false};
            if (p == 8) it.wa = B_PROFREE;
            if (uses[s] > 0) it.wa = empty_code(s);
            sc.slot[c][order[p]] = (unsigned char)(s | ((uses[s] & 1) << 4));
            uses[s]++;
            items[c][cnt[c]++] = it;
        };
        if (c == 0) {
            for (int p = 0; p < NKV; p++) put_kv(p, p < 26 ? p % NSLOT : (p + 1) % NSLOT);
            for (int j = 0; j < 9; j++) {
                const int last = ((j + 1) * FOP - 1) / SLOT;
                items[c][cnt[c]++] = Item{72 + j, j * FOP / 1024, empty_code(last), empty_code(last - 1), B_T + j, 64.0 + j, (double)FOP, true};
            }
        } else {
            int ring[NSLOT], n = NSLOT - 1, at = 0, b = 0;
            for (int s = 0; s < NSLOT; s++) ring[s] = s;
            auto put_wo = [&](double tau, bool late) {
                while (late && ring[at] >= 11) if (++at == n) at = 0;
                const int s = ring[at];
                items[c][cnt[c]++] = Item{64 + b, s * 16, empty_code(s), 127, B_T + b, tau, (double)SLOT, late};
                hot.wo_slots |= (unsigned)s << (4 * b);
                for (int i = at; i + 1 < n; i++) ring[i] = ring[i + 1];
                n--; if (at == n) at = 0;
                b++;
            };
            for (int p = 0; p < NKV; p++) {
                if (b < t.wo_early && p >= t.wo_first + b * t.wo_step && ring[at] < 11) put_wo(p - 0.5, false);
                put_kv(p, ring[at]);
                if (++at == n) at = 0;
            }
            while (b < 8) put_wo(63.5, true);
            items[c][cnt[c]++] = Item{81, 11 * 16, empty_code(11), 127, B_T + 8, 80.0, (double)FOP, true};
        }
    }
    for (int b = 0; b < 8; b++)
        for (int i = 0; i < cnt[1]; i++)
            if (items[1][i].op == 64 + b) items[2][cnt[2]++] = Item{64 + b, b * 16, 127, 127, B_T + b, items[1][i].tau, (double)SLOT, items[1][i].late};
    items[2][cnt[2]++] = Item{81, 11 * 16, 127, 127, B_T + 8, 80.0, (double)FOP, true};
    const double mult[3] = {96, 32, 4};
    const double pro_bytes = 576.0 * (5 * D_MODEL + HQD) * 2, tile_bytes = (double)SLOT * 128;
    auto pos_of = [&](double tau) {
        double s = pro_bytes;
        for (int c = 0; c < 3; c++) for (int i = 0; i < cnt[c]; i++) if (items[c][i].tau < tau) s += mult[c] * items[c][i].bytes;
        return s;
    };
    for (int c = 0; c < 3; c++) {
        const int first = c < 2 ? NPRE : 0;
        for (int m = 0; m < MAXOPS; m++) {
            if (first + m >= cnt[c]) { sc.ops[c][m] = make_uint2(0u, 0u); continue; }
            const Item& it = items[c][first + m];
            const double lead = it.op == 81 ? t.lead_last : it.late ? t.lead_late : (it.tau < t.n_start ? t.lead_start : (it.tau < t.sw_tail ? t.lead_main : t.lead_tail));
            int gmin = (int)((pos_of(it.tau) - lead * tile_bytes) / 4096);
            if (gmin < 0) gmin = 0;
            sc.ops[c][m] = make_uint2((unsigned)it.wa | ((unsigned)it.wb << 8) | ((unsigned)it.full << 24),
                                      (unsigned)it.dst | ((unsigned)it.op << 8) | ((unsigned)gmin << 16));
        }
    }
    hot.poll_gap = 2 * t.poll_gap; hot.thr_y = t.thr_y; hot.thr_d = t.thr_d;
    hot.n_timed = t.n_timed; hot.t_kv0 = (int)(1.95 * t.t_kv0); hot.dt_kv = (int)(1.95 * t.dt_kv);
    hot.g_pw = (int)(pos_of(30.0) / 1024);
    hot.g_x = (int)(pos_of(60.0) / 1024);
    hot.g_kv0 = (int)((pro_bytes - t.lead_start * tile_bytes) / 1024);
}

}

extern "C" void kernel_launch(void* const* d_in, const int* in_sizes, int n_in, void* d_out, int out_size) {
    (void)in_sizes; (void)n_in; (void)out_size;
    static EncodeFn enc = nullptr;
    static Scratch* scr = nullptr;
    if (!enc) {
        cudaGetSymbolAddress((void**)&scr, g_scratch);
        void* fn = nullptr;
        cudaDriverEntryPointQueryResult qr;
        cudaGetDriverEntryPoint("cuTensorMapEncodeTiled", &fn, cudaEnableDefault, &qr);
        enc = (EncodeFn)fn;
        cudaFuncSetAttribute(fused_decode_kernel, cudaFuncAttributeMaxDynamicSharedMemorySize, SMEM_BYTES);
    }
    Sched sched;
    Hot hot;
    build_sched(g_tune, sched, hot);
    Maps maps;
    const int prom = CU_TENSOR_MAP_L2_PROMOTION_L2_128B, promkv = CU_TENSOR_MAP_L2_PROMOTION_NONE, promp = prom;
    make3d(enc, &maps.k, d_in[1], 262144, 2, 64, promkv);
    make3d(enc, &maps.v, d_in[2], 262144, 2, 64, promkv);
    make3d(enc, &maps.wd, d_in[8], FF, 9, 16, promkv);
    make2d(enc, &maps.wmod, d_in[10], D_MODEL, N_MOD, 32, 192, CU_TENSOR_MAP_SWIZZLE_64B, promp);
    make2d(enc, &maps.wq, d_in[3], D_MODEL, HQD, 32, 192, CU_TENSOR_MAP_SWIZZLE_64B, promp);
    make2d(enc, &maps.wo, d_in[4], HQD, D_MODEL, 32, 256, CU_TENSOR_MAP_SWIZZLE_64B, prom);
    make2d(enc, &maps.g32, d_in[6], D_MODEL, FF, 32, 192, CU_TENSOR_MAP_SWIZZLE_64B, prom);
    make2d(enc, &maps.u32, d_in[7], D_MODEL, FF, 32, 192, CU_TENSOR_MAP_SWIZZLE_64B, prom);
    make2d(enc, &maps.g16, d_in[6], D_MODEL, FF, 16, 192, CU_TENSOR_MAP_SWIZZLE_32B, prom);
    make2d(enc, &maps.u16, d_in[7], D_MODEL, FF, 16, 192, CU_TENSOR_MAP_SWIZZLE_32B, prom);
    make2d(enc, &maps.wm16, d_in[10], D_MODEL, N_MOD, 16, 192, CU_TENSOR_MAP_SWIZZLE_32B, prom);
    cudaLaunchConfig_t cfg = {};
    cfg.gridDim = dim3(NCTA); cfg.blockDim = dim3(NTHREADS); cfg.dynamicSmemBytes = SMEM_BYTES; cfg.stream = cudaStreamPerThread;
    cudaLaunchAttribute at[1];
    at[0].id = cudaLaunchAttributeCooperative; at[0].val.cooperative = 1;
    cfg.attrs = at; cfg.numAttrs = 1;
    cudaLaunchKernelEx(&cfg, fused_decode_kernel, scr, (const __nv_bfloat16*)d_in[0], (const __nv_bfloat16*)d_in[9], (__nv_bfloat16*)d_out, hot, maps, sched);
}
```
